```python
import torch

def _softmax(x, axis=-1):
    return torch.softmax(x, dim=axis)
def _gelu(x):
    return torch.nn.functional.gelu(x, approximate="tanh")
def _silu(x):
    return torch.nn.functional.silu(x)
def _sigmoid(x):
    return torch.sigmoid(x)
def _layernorm(x, axis=-1, eps=1e-5):
    m = x.mean(dim=axis, keepdim=True)
    v = x.var(dim=axis, keepdim=True, unbiased=False)
    return (x - m) / torch.sqrt(v + eps)
def _scatter_add(tgt, idx, src, axis=0):
    return tgt.clone().index_add_(axis, idx, src)
def _segment_sum(src, seg, n):
    out = torch.zeros((n,) + src.shape[1:], dtype=src.dtype)
    return out.index_add_(0, seg, src)
def _pad(x, pw):
    flat = tuple(v for pair in reversed(pw) for v in pair)
    return torch.nn.functional.pad(x, flat)

kernel_name = 'gated_mix__mha_block__sliding_local_dilated__prompt'

def setup_inputs():

    _w = (lambda a: (lambda t: t.to(torch.bfloat16) if t.is_floating_point() else t)(torch.as_tensor(a)))
    def _A_setup():
        B, S, D, H = 1, 2048, 576, 32
        return {
            "x": _w((lambda *s: torch.randn(*s, dtype=torch.bfloat16) * 0.05)(B, S, D)),
            "wqkv": _w((lambda *s: torch.randn(*s, dtype=torch.bfloat16) * 1.6)(D, 3 * D)),
            "wo": _w((lambda *s: torch.randn(*s, dtype=torch.bfloat16) * 0.1)(D, D)),
        }
    _A_in = _A_setup()

    def _B_setup():
        B, S, D = 1, 2048, 576
        return {
            "x": _w((lambda *s: torch.randn(*s, dtype=torch.bfloat16) * 0.05)(B, S, D)),
            "wqkv": _w((lambda *s: torch.randn(*s, dtype=torch.bfloat16) * 1.6)(D, 3 * D)),
            "wo": _w((lambda *s: torch.randn(*s, dtype=torch.bfloat16) * 0.05)(D, D)),
        }
    _B_in = _B_setup()

    return {
        "A_x": _A_in["x"],
        "A_wqkv": _A_in["wqkv"],
        "A_wo": _A_in["wo"],
        "B_x": _B_in["x"],
        "B_wqkv": _B_in["wqkv"],
        "B_wo": _B_in["wo"],
        "gate_w": _w((lambda *s: torch.randn(*s, dtype=torch.bfloat16) * 0.05)(576) * 16.0),
    }

def reference(A_x, A_wqkv, A_wo, B_x, B_wqkv, B_wo, gate_w):
    def _A_ref(x, wqkv, wo):
        B, S, D = x.shape
        H = 32
        Dh = D // H
        qkv = (lambda x, *d: x.permute(*d))((x @ wqkv).reshape(B, S, 3, H, Dh), 2, 0, 3, 1, 4)
        q, k, v = qkv[0], qkv[1], qkv[2]
        scores = torch.einsum("bhqd,bhkd->bhqk", q, k) * (Dh ** -0.5)
        p = _softmax(scores, axis=-1)
        o = torch.einsum("bhqk,bhkd->bhqd", p, v)
        return (lambda x, *d: x.permute(*d))(o, 0, 2, 1, 3).reshape(B, S, D) @ wo

    def _B_ref(x, wqkv, wo):
        B, S, D = x.shape
        H = 32; Dh = D // H
        W, dil = 8, 2
        qkv = (lambda x, *d: x.permute(*d))((x @ wqkv).reshape(B, S, 3, H, Dh), 2, 0, 3, 1, 4)
        q, k, v = qkv[0], qkv[1], qkv[2]
        scale = Dh ** -0.5
        pos = torch.arange(S)
        off = torch.arange(W) * dil
        idx = pos[:, None] - off[None, :]
        mask = idx >= 0
        idx_c = torch.where(mask, idx, 0).reshape(-1)
        kg = k[:, :, idx_c, :].reshape(B, H, S, W, Dh)
        vg = v[:, :, idx_c, :].reshape(B, H, S, W, Dh)
        logits = torch.einsum("bhsd,bhswd->bhsw", q, kg) * scale
        logits = torch.where(mask[None, None, :, :], logits, -1e9)
        attn = _softmax(logits, axis=-1)
        o = torch.einsum("bhsw,bhswd->bhsd", attn, vg)
        return (lambda x, *d: x.permute(*d))(o, 0, 2, 1, 3).reshape(B, S, D) @ wo

    x = A_x
    g = _sigmoid((x * gate_w).sum(-1, keepdims=True))
    a = _A_ref(x, A_wqkv, A_wo)
    b = _B_ref(x, B_wqkv, B_wo)
    return g * a + (1 - g) * b
```

```cpp
#include <cuda_runtime.h>
#include <cuda_bf16.h>
#include <cuda.h>
#include <stdint.h>

constexpr int SEQ = 2048, DM = 576, DH = 18, N3 = 1728;
constexpr int GRP = 384;
constexpr int SLICE = 256 * GRP;
constexpr float QSCALE = 0.23570226039551584f * 1.4426950408889634f;
constexpr uint32_t POLY_MASK = 0x7777u;

__device__ __align__(1024) uint8_t g_img[192 * SLICE];
__device__ float2 g_gate[SEQ];
__device__ __align__(1024) __nv_bfloat16 g_o[SEQ * 2 * DM];

__device__ __forceinline__ uint32_t smem_u32(const void* p) { return (uint32_t)__cvta_generic_to_shared(p); }
__device__ __forceinline__ void mbar_init(uint32_t bar, int cnt) { asm volatile("mbarrier.init.shared::cta.b64 [%0], %1;" :: "r"(bar), "r"(cnt)); }
__device__ __forceinline__ void mbar_expect(uint32_t bar, uint32_t bytes) { asm volatile("mbarrier.arrive.expect_tx.shared::cta.b64 _, [%0], %1;" :: "r"(bar), "r"(bytes) : "memory"); }
__device__ __forceinline__ void mbar_arrive(uint32_t bar) { asm volatile("mbarrier.arrive.shared::cta.b64 _, [%0];" :: "r"(bar) : "memory"); }
__device__ __forceinline__ void mbar_wait(uint32_t bar, uint32_t par) {
  uint32_t ok; int it = 0;
  do { asm volatile("{\n.reg .pred p;\nmbarrier.try_wait.parity.shared::cta.b64 p, [%1], %2;\nselp.u32 %0, 1, 0, p;\n}" : "=r"(ok) : "r"(bar), "r"(par) : "memory");
  } while (!ok && ++it < (1 << 22));
}
__device__ __forceinline__ void bulk_g2s(uint32_t dst, const void* src, uint32_t bytes, uint32_t bar) {
  asm volatile("cp.async.bulk.shared::cluster.global.mbarrier::complete_tx::bytes [%0], [%1], %2, [%3];" :: "r"(dst), "l"(src), "r"(bytes), "r"(bar) : "memory");
}
__device__ __forceinline__ void bulk_s2g(void* dst, uint32_t src, uint32_t bytes) {
  asm volatile("cp.async.bulk.global.shared::cta.bulk_group [%0], [%1], %2;" :: "l"(dst), "r"(src), "r"(bytes) : "memory");
}
__device__ __forceinline__ void tma2d(uint32_t dst, const CUtensorMap* tm, int c0, int c1, uint32_t bar) {
  asm volatile("cp.async.bulk.tensor.2d.shared::cluster.global.mbarrier::complete_tx::bytes [%0], [%1, {%3, %4}], [%2];"
               :: "r"(dst), "l"(tm), "r"(bar), "r"(c0), "r"(c1) : "memory");
}
__device__ __forceinline__ void fence_async() { asm volatile("fence.proxy.async.shared::cta;" ::: "memory"); }
__device__ __forceinline__ void wg_fence() { asm volatile("wgmma.fence.sync.aligned;" ::: "memory"); }
__device__ __forceinline__ void wg_commit() { asm volatile("wgmma.commit_group.sync.aligned;" ::: "memory"); }
template<int N> __device__ __forceinline__ void wg_wait() { asm volatile("wgmma.wait_group.sync.aligned %0;" :: "n"(N) : "memory"); }
__device__ __forceinline__ uint64_t mkdesc(uint32_t addr, uint32_t lbo, uint32_t sbo, uint32_t swz) {
  uint64_t d = (uint64_t)((addr & 0x3FFFF) >> 4) | ((uint64_t)(lbo >> 4) << 16) | ((uint64_t)(sbo >> 4) << 32) | ((uint64_t)swz << 62);
  asm volatile("" : "+l"(d));
  return d;
}
template<int N> __device__ __forceinline__ void pin(float (&r)[N]) {
#pragma unroll
  for (int i = 0; i < N; i++) asm volatile("" : "+f"(r[i]) :: "memory");
}
template<int N> __device__ __forceinline__ void pin(uint32_t (&r)[N]) {
#pragma unroll
  for (int i = 0; i < N; i++) asm volatile("" : "+r"(r[i]) :: "memory");
}
__device__ __forceinline__ float ex2(float x) { float y; asm("ex2.approx.ftz.f32 %0, %1;" : "=f"(y) : "f"(x)); return y; }
__device__ __forceinline__ uint32_t pack_bf16(float lo, float hi) { uint32_t r; asm("cvt.rn.bf16x2.f32 %0, %1, %2;" : "=r"(r) : "f"(hi), "f"(lo)); return r; }
__device__ __forceinline__ uint32_t hfma2(uint32_t a, uint32_t b, uint32_t c) { uint32_t r; asm("fma.rn.bf16x2 %0, %1, %2, %3;" : "=r"(r) : "r"(a), "r"(b), "r"(c)); return r; }
__device__ __forceinline__ float bf_lo(uint32_t v) { return __uint_as_float(v << 16); }
__device__ __forceinline__ float bf_hi(uint32_t v) { return __uint_as_float(v & 0xFFFF0000u); }
__device__ __forceinline__ float bf_round(float x) { return __bfloat162float(__float2bfloat16(x)); }
__device__ __forceinline__ void sts32(uint32_t a, uint32_t v) { asm volatile("st.shared.u32 [%0], %1;" :: "r"(a), "r"(v) : "memory"); }
__device__ __forceinline__ void sts64(uint32_t a, uint32_t v0, uint32_t v1) { asm volatile("st.shared.v2.u32 [%0], {%1, %2};" :: "r"(a), "r"(v0), "r"(v1) : "memory"); }
__device__ __forceinline__ void ldsm4(uint32_t (&r)[4], uint32_t a) { asm volatile("ldmatrix.sync.aligned.m8n8.x4.shared.b16 {%0,%1,%2,%3}, [%4];" : "=r"(r[0]), "=r"(r[1]), "=r"(r[2]), "=r"(r[3]) : "r"(a) : "memory"); }
__device__ __forceinline__ void ldsm4t(uint32_t (&r)[4], uint32_t a) { asm volatile("ldmatrix.sync.aligned.m8n8.x4.trans.shared.b16 {%0,%1,%2,%3}, [%4];" : "=r"(r[0]), "=r"(r[1]), "=r"(r[2]), "=r"(r[3]) : "r"(a) : "memory"); }
__device__ __forceinline__ void ldsm2(uint32_t (&r)[2], uint32_t a) { asm volatile("ldmatrix.sync.aligned.m8n8.x2.shared.b16 {%0,%1}, [%2];" : "=r"(r[0]), "=r"(r[1]) : "r"(a) : "memory"); }
__device__ __forceinline__ void mma16816(float (&c)[4], uint32_t a0, uint32_t a1, uint32_t a2, uint32_t a3, uint32_t b0, uint32_t b1) {
  asm("mma.sync.aligned.m16n8k16.row.col.f32.bf16.bf16.f32 {%0,%1,%2,%3}, {%4,%5,%6,%7}, {%8,%9}, {%0,%1,%2,%3};"
      : "+f"(c[0]), "+f"(c[1]), "+f"(c[2]), "+f"(c[3]) : "r"(a0), "r"(a1), "r"(a2), "r"(a3), "r"(b0), "r"(b1));
}
__device__ __forceinline__ void mma1688(float (&c)[4], uint32_t a0, uint32_t a1, uint32_t b0) {
  asm("mma.sync.aligned.m16n8k8.row.col.f32.bf16.bf16.f32 {%0,%1,%2,%3}, {%4,%5}, {%6}, {%0,%1,%2,%3};"
      : "+f"(c[0]), "+f"(c[1]), "+f"(c[2]), "+f"(c[3]) : "r"(a0), "r"(a1), "r"(b0));
}
__device__ __forceinline__ void pdl_wait() { asm volatile("griddepcontrol.wait;" ::: "memory"); }
__device__ __forceinline__ void pdl_launch() { asm volatile("griddepcontrol.launch_dependents;"); }

__device__ __forceinline__ void wgmma_ss_n216_mn(float (&d)[108], uint64_t descA, uint64_t descB, int scaleD) {
  asm volatile("{\n.reg .pred p;\nsetp.ne.b32 p, %110, 0;\n"
    "wgmma.mma_async.sync.aligned.m64n216k16.f32.bf16.bf16 {%0, %1, %2, %3, %4, %5, %6, %7, %8, %9, %10, %11, %12, %13, %14, %15, %16, %17, %18, %19, %20, %21, %22, %23, %24, %25, %26, %27, %28, %29, %30, %31, %32, %33, %34, %35, %36, %37, %38, %39, %40, %41, %42, %43, %44, %45, %46, %47, %48, %49, %50, %51, %52, %53, %54, %55, %56, %57, %58, %59, %60, %61, %62, %63, %64, %65, %66, %67, %68, %69, %70, %71, %72, %73, %74, %75, %76, %77, %78, %79, %80, %81, %82, %83, %84, %85, %86, %87, %88, %89, %90, %91, %92, %93, %94, %95, %96, %97, %98, %99, %100, %101, %102, %103, %104, %105, %106, %107}, %108, %109, p, 1, 1, 0, 1;\n}\n"
    : "+f"(d[0]), "+f"(d[1]), "+f"(d[2]), "+f"(d[3]), "+f"(d[4]), "+f"(d[5]), "+f"(d[6]), "+f"(d[7]), "+f"(d[8]), "+f"(d[9]), "+f"(d[10]), "+f"(d[11]), "+f"(d[12]), "+f"(d[13]), "+f"(d[14]), "+f"(d[15]), "+f"(d[16]), "+f"(d[17]), "+f"(d[18]), "+f"(d[19]), "+f"(d[20]), "+f"(d[21]), "+f"(d[22]), "+f"(d[23]), "+f"(d[24]), "+f"(d[25]), "+f"(d[26]), "+f"(d[27]), "+f"(d[28]), "+f"(d[29]), "+f"(d[30]), "+f"(d[31]), "+f"(d[32]), "+f"(d[33]), "+f"(d[34]), "+f"(d[35]), "+f"(d[36]), "+f"(d[37]), "+f"(d[38]), "+f"(d[39]), "+f"(d[40]), "+f"(d[41]), "+f"(d[42]), "+f"(d[43]), "+f"(d[44]), "+f"(d[45]), "+f"(d[46]), "+f"(d[47]), "+f"(d[48]), "+f"(d[49]), "+f"(d[50]), "+f"(d[51]), "+f"(d[52]), "+f"(d[53]), "+f"(d[54]), "+f"(d[55]), "+f"(d[56]), "+f"(d[57]), "+f"(d[58]), "+f"(d[59]), "+f"(d[60]), "+f"(d[61]), "+f"(d[62]), "+f"(d[63]), "+f"(d[64]), "+f"(d[65]), "+f"(d[66]), "+f"(d[67]), "+f"(d[68]), "+f"(d[69]), "+f"(d[70]), "+f"(d[71]), "+f"(d[72]), "+f"(d[73]), "+f"(d[74]), "+f"(d[75]), "+f"(d[76]), "+f"(d[77]), "+f"(d[78]), "+f"(d[79]), "+f"(d[80]), "+f"(d[81]), "+f"(d[82]), "+f"(d[83]), "+f"(d[84]), "+f"(d[85]), "+f"(d[86]), "+f"(d[87]), "+f"(d[88]), "+f"(d[89]), "+f"(d[90]), "+f"(d[91]), "+f"(d[92]), "+f"(d[93]), "+f"(d[94]), "+f"(d[95]), "+f"(d[96]), "+f"(d[97]), "+f"(d[98]), "+f"(d[99]), "+f"(d[100]), "+f"(d[101]), "+f"(d[102]), "+f"(d[103]), "+f"(d[104]), "+f"(d[105]), "+f"(d[106]), "+f"(d[107])
    : "l"(descA), "l"(descB), "r"(scaleD));
}

__device__ __forceinline__ void wgmma_ss_n72_mn(float (&d)[36], uint64_t descA, uint64_t descB, int scaleD) {
  asm volatile("{\n.reg .pred p;\nsetp.ne.b32 p, %38, 0;\n"
    "wgmma.mma_async.sync.aligned.m64n72k16.f32.bf16.bf16 {%0, %1, %2, %3, %4, %5, %6, %7, %8, %9, %10, %11, %12, %13, %14, %15, %16, %17, %18, %19, %20, %21, %22, %23, %24, %25, %26, %27, %28, %29, %30, %31, %32, %33, %34, %35}, %36, %37, p, 1, 1, 0, 1;\n}\n"
    : "+f"(d[0]), "+f"(d[1]), "+f"(d[2]), "+f"(d[3]), "+f"(d[4]), "+f"(d[5]), "+f"(d[6]), "+f"(d[7]), "+f"(d[8]), "+f"(d[9]), "+f"(d[10]), "+f"(d[11]), "+f"(d[12]), "+f"(d[13]), "+f"(d[14]), "+f"(d[15]), "+f"(d[16]), "+f"(d[17]), "+f"(d[18]), "+f"(d[19]), "+f"(d[20]), "+f"(d[21]), "+f"(d[22]), "+f"(d[23]), "+f"(d[24]), "+f"(d[25]), "+f"(d[26]), "+f"(d[27]), "+f"(d[28]), "+f"(d[29]), "+f"(d[30]), "+f"(d[31]), "+f"(d[32]), "+f"(d[33]), "+f"(d[34]), "+f"(d[35])
    : "l"(descA), "l"(descB), "r"(scaleD));
}

template<int SD> __device__ __forceinline__ void wgmma_rs_n64_k(float (&d)[32], uint32_t a0, uint32_t a1, uint32_t a2, uint32_t a3, uint64_t descB) {
  asm volatile("{\n.reg .pred p;\nsetp.ne.b32 p, %37, 0;\n"
    "wgmma.mma_async.sync.aligned.m64n64k16.f32.bf16.bf16 {%0, %1, %2, %3, %4, %5, %6, %7, %8, %9, %10, %11, %12, %13, %14, %15, %16, %17, %18, %19, %20, %21, %22, %23, %24, %25, %26, %27, %28, %29, %30, %31}, {%32, %33, %34, %35}, %36, p, 1, 1, 0;\n}\n"
    : "+f"(d[0]), "+f"(d[1]), "+f"(d[2]), "+f"(d[3]), "+f"(d[4]), "+f"(d[5]), "+f"(d[6]), "+f"(d[7]), "+f"(d[8]), "+f"(d[9]), "+f"(d[10]), "+f"(d[11]), "+f"(d[12]), "+f"(d[13]), "+f"(d[14]), "+f"(d[15]), "+f"(d[16]), "+f"(d[17]), "+f"(d[18]), "+f"(d[19]), "+f"(d[20]), "+f"(d[21]), "+f"(d[22]), "+f"(d[23]), "+f"(d[24]), "+f"(d[25]), "+f"(d[26]), "+f"(d[27]), "+f"(d[28]), "+f"(d[29]), "+f"(d[30]), "+f"(d[31])
    : "r"(a0), "r"(a1), "r"(a2), "r"(a3), "l"(descB), "n"(SD));
}

template<int SD> __device__ __forceinline__ void wgmma_rs_n24_mn(float (&d)[12], uint32_t a0, uint32_t a1, uint32_t a2, uint32_t a3, uint64_t descB) {
  asm volatile("{\n.reg .pred p;\nsetp.ne.b32 p, %17, 0;\n"
    "wgmma.mma_async.sync.aligned.m64n24k16.f32.bf16.bf16 {%0, %1, %2, %3, %4, %5, %6, %7, %8, %9, %10, %11}, {%12, %13, %14, %15}, %16, p, 1, 1, 1;\n}\n"
    : "+f"(d[0]), "+f"(d[1]), "+f"(d[2]), "+f"(d[3]), "+f"(d[4]), "+f"(d[5]), "+f"(d[6]), "+f"(d[7]), "+f"(d[8]), "+f"(d[9]), "+f"(d[10]), "+f"(d[11])
    : "r"(a0), "r"(a1), "r"(a2), "r"(a3), "l"(descB), "n"(SD));
}


constexpr int K1_X = 0, K1_W = 147456, K1_STG = 212992, K1_BAR = 225280, K1_SMEM = 225280 + 256 + 1024;

__device__ __forceinline__ void k1_unit(const uint32_t (&pk)[54], int u, int rh, int br, uint32_t stg, const uint32_t (&off)[9],
                                        int ct, int row0, int lane) {
#pragma unroll
  for (int j = 0; j < 9; j++) sts32(stg + off[j], pk[(9 * u + j) * 2 + rh]);
  const int sl = ct * 12 + u * 4, type = sl >> 5, rg = row0 + rh * 8;
  uint32_t c1 = 0, c2 = 0;
  if (type == 2) c1 = 0x00003F80u;
  else if (br == 0) {
    if (type == 0) { c1 = 0x3F803F80u; c2 = 0x00003F80u; }
    else if ((POLY_MASK >> ((rg >> 3) & 15)) & 1) { c1 = (lane & 1) ? 0x43F84780u : 0x42FE4780u; c2 = 0x00003B80u; }
    else { c1 = 0x3F160000u; c2 = 0x00003A00u; }
  }
  const uint32_t a = stg + (lane >> 3) * GRP + 256 + (lane & 7) * 16;
  sts32(a + 4, c1); sts64(a + 8, c2, 0);
  fence_async();
  __syncwarp();
  if (lane < 4) {
    bulk_s2g(g_img + (size_t)(br * 96 + sl + lane) * SLICE + (rg >> 3) * GRP, stg + lane * GRP, GRP);
    asm volatile("cp.async.bulk.commit_group;" ::: "memory");
  }
}
__device__ __forceinline__ void k1_pack(uint32_t (&pk)[54], const float (&acc)[108], int ct) {
#pragma unroll
  for (int u = 0; u < 3; u++) {
    const float sc = (ct * 12 + u * 4) < 32 ? QSCALE : 1.f;
#pragma unroll
    for (int i = 0; i < 18; i++) pk[18 * u + i] = pack_bf16(acc[36 * u + 2 * i] * sc, acc[36 * u + 2 * i + 1] * sc);
  }
}
__device__ __forceinline__ void k1_step(float (&acc)[108], int it, int gs, uint64_t dX, uint64_t dW, uint32_t wfull, uint32_t wempty, int lane) {
  const int s = gs & 3;
  mbar_wait(wfull + 8 * s, (gs >> 2) & 1);
  const uint64_t da = dX + (uint64_t)((it >> 1) * 1024 + (it & 1) * 4), db = dW + (uint64_t)(s * 1024);
  wg_fence();
  wgmma_ss_n216_mn(acc, da, db, it);
  wgmma_ss_n216_mn(acc, da + 2, db + 128, 1);
  wg_commit();
  wg_wait<1>();
  if (it > 0 && lane == 0) mbar_arrive(wempty + 8 * ((gs - 1) & 3));
}

__global__ void __launch_bounds__(384, 1) k1_qkv(const __grid_constant__ CUtensorMap tmX, const __grid_constant__ CUtensorMap tmWA,
                                                  const __grid_constant__ CUtensorMap tmWB, const __nv_bfloat16* __restrict__ x,
                                                  const __nv_bfloat16* __restrict__ gate_w) {
  extern __shared__ uint8_t smem_raw[];
  const uint32_t sb = (smem_u32(smem_raw) + 1023) & ~1023u;
  const uint32_t xfull = sb + K1_BAR, wfull = xfull + 72, wempty = wfull + 32;
  const int tid = threadIdx.x, warp = __shfl_sync(~0u, tid >> 5, 0), lane = tid & 31;
  const int rt = blockIdx.x & 15, ct = blockIdx.x >> 4;
  if (tid == 0) {
    for (int i = 0; i < 9; i++) mbar_init(xfull + 8 * i, 1);
    for (int i = 0; i < 4; i++) { mbar_init(wfull + 8 * i, 1); mbar_init(wempty + 8 * i, 8); }
    asm volatile("fence.mbarrier_init.release.cluster;" ::: "memory");
  }
  __syncthreads();
  pdl_launch();
  if (warp >= 8) {
    asm volatile("setmaxnreg.dec.sync.aligned.u32 24;");
    if (warp == 8) {
      if (lane == 0) {
        for (int gs = 0; gs < 36; gs++) {
          const int s = gs & 3;
          if (gs >= 4) mbar_wait(wempty + 8 * s, ((gs >> 2) - 1) & 1);
          mbar_expect(wfull + 8 * s, 16384);
          const CUtensorMap* tm = gs < 18 ? &tmWA : &tmWB;
          const int k0 = (gs < 18 ? gs : gs - 18) * 32;
#pragma unroll
          for (int a = 0; a < 4; a++) tma2d(sb + K1_W + s * 16384 + a * 4096, tm, ct * 216 + a * 64, k0, wfull + 8 * s);
        }
      }
    } else if (warp == 9) {
      if (lane == 0) {
        for (int kb = 0; kb < 9; kb++) {
          mbar_expect(xfull + 8 * kb, 16384);
          tma2d(sb + K1_X + kb * 16384, &tmX, kb * 64, rt * 128, xfull + 8 * kb);
        }
      }
    } else {
      for (int r = warp - 10; r < 16; r += 2) {
        const int row = blockIdx.x * 16 + r;
        const uint32_t* xr = (const uint32_t*)(x + row * DM);
        const uint32_t* gw = (const uint32_t*)gate_w;
        float s = 0.f;
#pragma unroll
        for (int i = 0; i < 9; i++) {
          const uint32_t a = __ldg(xr + lane + 32 * i), b = __ldg(gw + lane + 32 * i);
          s += bf_round(bf_lo(a) * bf_lo(b)) + bf_round(bf_hi(a) * bf_hi(b));
        }
#pragma unroll
        for (int o = 16; o > 0; o >>= 1) s += __shfl_xor_sync(~0u, s, o);
        if (lane == 0) {
          const float z = bf_round(s);
          const float g = bf_round(1.f / (1.f + __expf(-z)));
          g_gate[row] = make_float2(g, bf_round(1.f - g));
        }
      }
    }
  } else {
    asm volatile("setmaxnreg.inc.sync.aligned.u32 240;");
    float acc[108]; uint32_t pk[54], off[9];
    const uint64_t dX = mkdesc(sb + K1_X + (warp >> 2) * 8192, 16, 1024, 1);
    const uint64_t dW = mkdesc(sb + K1_W, 4096, 1024, 1);
    const int row0 = rt * 128 + warp * 16;
#pragma unroll
    for (int j = 0; j < 9; j++) {
      const int p = 4 * j + (lane & 3), hh = p / 9, r9 = p - 9 * hh;
      off[j] = hh * GRP + (r9 >> 2) * 128 + (r9 & 3) * 4 + (lane >> 2) * 16;
    }
#pragma unroll 1
    for (int it = 0; it < 18; it++) {
      if (!(it & 1)) mbar_wait(xfull + 8 * (it >> 1), 0);
      k1_step(acc, it, it, dX, dW, wfull, wempty, lane);
    }
    wg_wait<0>(); pin(acc);
    if (lane == 0) mbar_arrive(wempty + 8 * (17 & 3));
    k1_pack(pk, acc, ct);
    pin(pk);
#pragma unroll
    for (int v = 0; v < 6; v++) {
#pragma unroll 1
      for (int it = 2 * v; it < 2 * v + 2; it++) k1_step(acc, it, 18 + it, dX, dW, wfull, wempty, lane);
      if (v) { if (lane < 4) asm volatile("cp.async.bulk.wait_group.read 0;" ::: "memory"); __syncwarp(); }
      k1_unit(pk, v >> 1, v & 1, 0, sb + K1_STG + warp * 1536, off, ct, row0, lane);
    }
#pragma unroll 1
    for (int it = 12; it < 18; it++) k1_step(acc, it, 18 + it, dX, dW, wfull, wempty, lane);
    wg_wait<0>(); pin(acc);
    k1_pack(pk, acc, ct);
#pragma unroll
    for (int v = 0; v < 6; v++) k1_unit(pk, v >> 1, v & 1, 1, sb + K1_X + v * 16384 + warp * 2048, off, ct, row0, lane);
    if (lane < 4) asm volatile("cp.async.bulk.wait_group 0;" ::: "memory");
  }
}

constexpr int K2_K = 0, K2_V = SLICE, K2_C = 2 * SLICE, K2_BAR = 2 * SLICE + 24576, K2_SMEM = K2_BAR + 256 + 1024;
constexpr int K2_BSTG = SLICE - 66 * GRP;

template<int MASK> __device__ __forceinline__ void softmax64(const float (&s)[32], uint32_t (&p)[16], uint32_t khalf) {
#pragma unroll
  for (int i = 0; i < 16; i++) {
    if ((MASK >> (i >> 1)) & 1) {
      uint32_t U, M;
      asm("mad.lo.u32 %0, %1, 65536, %2;" : "=r"(U) : "r"(__float_as_uint(s[2 * i + 1])), "r"(__float_as_uint(s[2 * i])));
      asm("lop3.b32 %0, %1, 0x007F007F, %2, 0xEA;" : "=r"(M) : "r"(U), "r"(khalf));
      p[i] = hfma2(M, U, U & 0xFF80FF80u);
    } else {
      p[i] = pack_bf16(ex2(s[2 * i]), ex2(s[2 * i + 1]));
    }
  }
}
__device__ __forceinline__ void issue_S(float (&s)[32], const uint32_t (&q)[8], uint64_t kd) {
  wgmma_rs_n64_k<0>(s, q[0], q[1], q[2], q[3], kd);
  wgmma_rs_n64_k<1>(s, q[4], q[5], q[6], q[7], kd + 16 - (8ull << 16));
}
__device__ __forceinline__ void issue_PV(float (&o)[12], const uint32_t (&p)[16], uint64_t vd) {
#pragma unroll
  for (int k = 0; k < 4; k++) wgmma_rs_n24_mn<1>(o, p[4 * k], p[4 * k + 1], p[4 * k + 2], p[4 * k + 3], vd + k * 48);
}
__device__ __forceinline__ void load_q(uint32_t (&q)[8], const uint8_t* qimg, int row0, int lane) {
  const uint32_t* p = (const uint32_t*)(qimg + (row0 >> 3) * GRP) + lane;
  q[0] = __ldcg(p); q[1] = __ldcg(p + 96); q[2] = __ldcg(p + 32); q[3] = __ldcg(p + 128);
  q[4] = __ldcg(p + 64); q[5] = __ldcg(p + 160); q[6] = 0; q[7] = 0;
}
__device__ __forceinline__ float sq2(uint32_t v) { const float a = bf_lo(v), b = bf_hi(v); return a * a + b * b; }
__device__ __forceinline__ float q_norm2_max(const uint32_t (&q)[8], int lane) {
  const bool t0 = (lane & 3) == 0;
  float a = sq2(q[0]) + sq2(q[2]) + (t0 ? sq2(q[4]) : 0.f), b = sq2(q[1]) + sq2(q[3]) + (t0 ? sq2(q[5]) : 0.f);
  a += __shfl_xor_sync(~0u, a, 1); b += __shfl_xor_sync(~0u, b, 1);
  a += __shfl_xor_sync(~0u, a, 2); b += __shfl_xor_sync(~0u, b, 2);
  return (a != a || b != b) ? __int_as_float(0x7f800000) : fmaxf(a, b);
}
__device__ __forceinline__ bool store_o(const float (&o)[12], int row0, int rstep, int col0, int which, int lane) {
  const int g = lane >> 2, t = lane & 3;
  const float l0 = __shfl_sync(~0u, o[8], (lane & ~3) | 1), l1 = __shfl_sync(~0u, o[10], (lane & ~3) | 1);
  const int r0 = row0 + g * rstep, r1 = r0 + 8 * rstep;
  const float2 g0 = g_gate[r0], g1 = g_gate[r1];
  const float s0 = (which ? g0.y : g0.x) / l0, s1 = (which ? g1.y : g1.x) / l1;
  uint32_t* p0 = (uint32_t*)(g_o + r0 * (2 * DM) + col0) + t;
  uint32_t* p1 = (uint32_t*)(g_o + r1 * (2 * DM) + col0) + t;
  p0[0] = pack_bf16(o[0] * s0, o[1] * s0); p1[0] = pack_bf16(o[2] * s1, o[3] * s1);
  p0[4] = pack_bf16(o[4] * s0, o[5] * s0); p1[4] = pack_bf16(o[6] * s1, o[7] * s1);
  if (t == 0) { p0[8] = pack_bf16(o[8] * s0, o[9] * s0); p1[8] = pack_bf16(o[10] * s1, o[11] * s1); }
  float m = 0.f;
#pragma unroll
  for (int i = 0; i < 12; i++) m += fabsf(o[i]);
  return !(m < 1e38f) || !(l0 > 1e-18f) || !(l1 > 1e-18f);
}

__global__ void __launch_bounds__(384, 1) k2_attn() {
  extern __shared__ uint8_t smem_raw[];
  const uint32_t sb = (smem_u32(smem_raw) + 1023) & ~1023u;
  uint8_t* sp = smem_raw + (sb - smem_u32(smem_raw));
  const uint32_t full = sb + K2_BAR, bfull = full + 64;
  volatile float* s_kmax = (volatile float*)(sp + K2_BAR + 128);
  const int tid = threadIdx.x, warp = __shfl_sync(~0u, tid >> 5, 0), lane = tid & 31;
  const int wg = warp >> 2, wq = warp & 3;
  const int h = blockIdx.x >> 2, R0 = (blockIdx.x & 3) * 512;
  if (tid == 0) {
    for (int i = 0; i < 9; i++) mbar_init(full + 8 * i, 1);
    asm volatile("fence.mbarrier_init.release.cluster;" ::: "memory");
  }
  if (R0 == 0 && tid < 192) { sts32(sb + K2_K + K2_BSTG + tid * 4, 0); sts32(sb + K2_V + K2_BSTG + tid * 4, 0); }
  __syncthreads();
  pdl_launch();
  pdl_wait();
  const uint8_t* qA = g_img + (size_t)h * SLICE;
  const uint8_t* kA = g_img + (size_t)(32 + h) * SLICE;
  const uint8_t* vA = g_img + (size_t)(64 + h) * SLICE;
  if (tid == 0) {
    const int halo = R0 ? 2 * GRP : 0, base = (R0 >> 3) * GRP;
    mbar_expect(bfull, 64 * GRP * 3 + 2 * halo);
    bulk_g2s(sb + K2_C, g_img + (size_t)(96 + h) * SLICE + base, 64 * GRP, bfull);
    bulk_g2s(sb + K2_K + K2_BSTG + 2 * GRP - halo, g_img + (size_t)(128 + h) * SLICE + base - halo, 64 * GRP + halo, bfull);
    bulk_g2s(sb + K2_V + K2_BSTG + 2 * GRP - halo, g_img + (size_t)(160 + h) * SLICE + base - halo, 64 * GRP + halo, bfull);
    for (int s = 0; s < 5; s++) {
      mbar_expect(full + 8 * s, 24576);
      bulk_g2s(sb + K2_K + s * 12288, kA + s * 12288, 12288, full + 8 * s);
      bulk_g2s(sb + K2_V + s * 12288, vA + s * 12288, 12288, full + 8 * s);
    }
  }
  mbar_wait(bfull, 0);
#pragma unroll 1
  for (int blk = warp; blk < 32; blk += 12) {
    const int rb = (blk >> 1) * 32 + (blk & 1);
    const int g = lane >> 2, t = lane & 3, l8 = lane & 7, m4 = lane >> 3;
    uint32_t qa[4], qb[2];
    { const int r = rb + 2 * (l8 + 8 * (m4 & 1));
      const uint32_t a = sb + K2_C + (r >> 3) * GRP + (r & 7) * 16;
      ldsm4(qa, a + (m4 >> 1) * 128); ldsm2(qb, a + 256); }
    float c[3][4]; uint32_t vf[3][4];
#pragma unroll
    for (int nb = 0; nb < 3; nb++) {
      const int r = rb + 2 * (8 * nb + l8);
      const uint32_t a = K2_BSTG + (r >> 3) * GRP + (r & 7) * 16 + (m4 < 3 ? m4 : 2) * 128;
      uint32_t kf[4];
      ldsm4(kf, sb + K2_K + a); ldsm4t(vf[nb], sb + K2_V + a);
      c[nb][0] = c[nb][1] = c[nb][2] = c[nb][3] = 0.f;
      mma16816(c[nb], qa[0], qa[1], qa[2], qa[3], kf[0], kf[1]);
      mma1688(c[nb], qb[0], qb[1], kf[2]);
    }
    const float NEG = __int_as_float(0xff800000);
    float m0 = NEG, m1 = NEG;
#pragma unroll
    for (int nb = 0; nb < 3; nb++)
#pragma unroll
      for (int e = 0; e < 4; e++) {
        const int j = 8 * nb + 2 * t + (e & 1), i = g + 8 * (e >> 1);
        const bool ok = j > i && j <= i + 8 && (R0 + rb - 16 + 2 * j) >= 0;
        c[nb][e] = ok ? c[nb][e] : NEG;
        if (e < 2) m0 = fmaxf(m0, c[nb][e]); else m1 = fmaxf(m1, c[nb][e]);
      }
    m0 = fmaxf(m0, __shfl_xor_sync(~0u, m0, 1)); m1 = fmaxf(m1, __shfl_xor_sync(~0u, m1, 1));
    m0 = fmaxf(m0, __shfl_xor_sync(~0u, m0, 2)); m1 = fmaxf(m1, __shfl_xor_sync(~0u, m1, 2));
    uint32_t pa[6];
#pragma unroll
    for (int nb = 0; nb < 3; nb++) {
      pa[2 * nb] = pack_bf16(ex2(c[nb][0] - m0), ex2(c[nb][1] - m0));
      pa[2 * nb + 1] = pack_bf16(ex2(c[nb][2] - m1), ex2(c[nb][3] - m1));
    }
    float o[12];
#pragma unroll
    for (int db = 0; db < 3; db++) {
      float d[4] = {0.f, 0.f, 0.f, 0.f};
      mma16816(d, pa[0], pa[1], pa[2], pa[3], vf[0][db], vf[1][db]);
      mma1688(d, pa[4], pa[5], vf[2][db]);
      o[4 * db] = d[0]; o[4 * db + 1] = d[1]; o[4 * db + 2] = d[2]; o[4 * db + 3] = d[3];
    }
    store_o(o, R0 + rb, 2, DM + h * DH, 1, lane);
  }
  __syncthreads();
  if (tid == 0) {
    for (int s = 5; s < 8; s++) {
      mbar_expect(full + 8 * s, 24576);
      bulk_g2s(sb + K2_K + s * 12288, kA + s * 12288, 12288, full + 8 * s);
      bulk_g2s(sb + K2_V + s * 12288, vA + s * 12288, 12288, full + 8 * s);
    }
  }
  const uint64_t kd0 = mkdesc(sb + K2_K, 128, GRP, 0), vd0 = mkdesc(sb + K2_V, GRP, 128, 0);
  uint32_t khalf = 0x3F003F00u; asm volatile("" : "+r"(khalf));
  float qn2 = 0.f; bool bad = false;
#pragma unroll 1
  for (int job = 0; job < 2; job++) {
    const int rowA = R0 + (job ? 384 : wg * 128) + wq * 16;
    const int st0 = job ? wg * 3 : 0, st1 = job ? min(st0 + 3, 8) : 8;
    uint32_t qa[8], qb[8];
    load_q(qa, qA, rowA, lane); load_q(qb, qA, rowA + 64, lane);
    qn2 = fmaxf(qn2, fmaxf(q_norm2_max(qa, lane), q_norm2_max(qb, lane)));
    float oa[12], ob[12], sA[32], sB[32]; uint32_t pA[16], pB[16];
#pragma unroll
    for (int i = 0; i < 12; i++) { oa[i] = 0.f; ob[i] = 0.f; }
#pragma unroll
    for (int i = 0; i < 32; i++) { sA[i] = 0.f; sB[i] = 0.f; }
    uint64_t kb = kd0 + (uint64_t)(st0 * 768), vb = vd0 + (uint64_t)(st0 * 768);
    mbar_wait(full + 8 * st0, 0);
    pin(oa); pin(ob); pin(sA); pin(sB); pin(qa); pin(qb);
    wg_fence(); issue_S(sA, qa, kb); wg_commit(); wg_wait<0>(); pin(sA);
#pragma unroll 1
    for (int st = st0; st < st1; st++, kb += 768, vb += 768) {
      mbar_wait(full + 8 * min(st + 1, 7), 0);
      wg_fence(); issue_S(sB, qb, kb); wg_commit();
#pragma unroll
      for (int u = 0; u < 4; u++) {
        if (u > 0) { wg_wait<1>(); pin(sA); }
        if (u & 1) softmax64<(POLY_MASK >> 8) & 255>(sA, pA, khalf); else softmax64<POLY_MASK & 255>(sA, pA, khalf);
        pin(pA);
        wg_fence();
        issue_PV(oa, pA, vb + u * 192);
        issue_S(sA, qa, kb + (u + 1) * 192);
        wg_commit();
        wg_wait<1>(); pin(sB);
        if (u & 1) softmax64<(POLY_MASK >> 8) & 255>(sB, pB, khalf); else softmax64<POLY_MASK & 255>(sB, pB, khalf);
        pin(pB);
        wg_fence();
        issue_PV(ob, pB, vb + u * 192);
        if (u < 3) issue_S(sB, qb, kb + (u + 1) * 192);
        wg_commit();
      }
      wg_wait<0>(); pin(sA); pin(oa); pin(ob);
    }
    if (job == 1) {
      float* cb = (float*)(sp + K2_C);
      if (wg > 0) {
#pragma unroll
        for (int i = 0; i < 12; i++) { cb[((wg - 1) * 24 + i) * 128 + (tid & 127)] = oa[i]; cb[((wg - 1) * 24 + 12 + i) * 128 + (tid & 127)] = ob[i]; }
      }
      if (wg == 2) {
        float km = 0.f;
#pragma unroll 4
        for (int r = tid & 127; r < SEQ; r += 128) {
          const uint8_t* kp = sp + K2_K + (r >> 3) * GRP + (r & 7) * 16;
          const uint4 a = *(const uint4*)kp, b = *(const uint4*)(kp + 128); const uint32_t c = *(const uint32_t*)(kp + 256);
          uint32_t acc = hfma2(c, c, 0);
          acc = hfma2(a.x, a.x, acc); acc = hfma2(a.y, a.y, acc); acc = hfma2(a.z, a.z, acc); acc = hfma2(a.w, a.w, acc);
          acc = hfma2(b.x, b.x, acc); acc = hfma2(b.y, b.y, acc); acc = hfma2(b.z, b.z, acc); acc = hfma2(b.w, b.w, acc);
          const float n2 = bf_lo(acc) + bf_hi(acc);
          km = (n2 != n2) ? __int_as_float(0x7f800000) : fmaxf(km, n2);
        }
#pragma unroll
        for (int o = 16; o > 0; o >>= 1) km = fmaxf(km, __shfl_xor_sync(~0u, km, o));
        if (lane == 0) s_kmax[wq] = km;
      }
      __syncthreads();
      if (wg == 0) {
#pragma unroll
        for (int i = 0; i < 12; i++) {
          oa[i] += cb[i * 128 + tid] + cb[(24 + i) * 128 + tid];
          ob[i] += cb[(12 + i) * 128 + tid] + cb[(36 + i) * 128 + tid];
        }
      }
    }
    if (job == 0 || wg == 0) {
      bad |= store_o(oa, rowA, 1, h * DH, 0, lane);
      bad |= store_o(ob, rowA + 64, 1, h * DH, 0, lane);
    }
  }
  {
    const float km = fmaxf(fmaxf(s_kmax[0], s_kmax[1]), fmaxf(s_kmax[2], s_kmax[3]));
    bad |= !(qn2 * km * 1.1f <= 110.f * 110.f);
  }
  if (__syncthreads_or(bad)) {
#pragma unroll 1
    for (int tile = wg; tile < 8; tile += 3) {
      const int row = R0 + tile * 64 + wq * 16;
      uint32_t q[8];
      load_q(q, qA, row, lane);
      if (lane & 3) { q[4] = 0; q[5] = 0; }
      float o[12], s[32]; uint32_t p[16];
#pragma unroll
      for (int i = 0; i < 12; i++) o[i] = 0.f;
#pragma unroll
      for (int i = 0; i < 32; i++) s[i] = 0.f;
      float m0 = __int_as_float(0xff800000), m1 = m0;
#pragma unroll 1
      for (int c = 0; c < 32; c++) {
        pin(s); pin(q);
        wg_fence(); issue_S(s, q, kd0 + (uint64_t)(c * 192)); wg_commit(); wg_wait<0>(); pin(s);
        float n0 = m0, n1 = m1;
#pragma unroll
        for (int b = 0; b < 8; b++) { n0 = fmaxf(n0, fmaxf(s[4 * b], s[4 * b + 1])); n1 = fmaxf(n1, fmaxf(s[4 * b + 2], s[4 * b + 3])); }
        n0 = fmaxf(n0, __shfl_xor_sync(~0u, n0, 1)); n1 = fmaxf(n1, __shfl_xor_sync(~0u, n1, 1));
        n0 = fmaxf(n0, __shfl_xor_sync(~0u, n0, 2)); n1 = fmaxf(n1, __shfl_xor_sync(~0u, n1, 2));
        const float a0 = ex2(m0 - n0), a1 = ex2(m1 - n1);
        m0 = n0; m1 = n1;
#pragma unroll
        for (int b = 0; b < 3; b++) { o[4 * b] *= a0; o[4 * b + 1] *= a0; o[4 * b + 2] *= a1; o[4 * b + 3] *= a1; }
#pragma unroll
        for (int b = 0; b < 8; b++) {
          p[2 * b] = pack_bf16(ex2(s[4 * b] - m0), ex2(s[4 * b + 1] - m0));
          p[2 * b + 1] = pack_bf16(ex2(s[4 * b + 2] - m1), ex2(s[4 * b + 3] - m1));
        }
        pin(o); pin(p);
        wg_fence(); issue_PV(o, p, vd0 + (uint64_t)(c * 192)); wg_commit(); wg_wait<0>(); pin(o);
      }
      store_o(o, row, 1, h * DH, 0, lane);
    }
  }
}

constexpr int K3_A = 0, K3_W = 49152, K3_BAR = K3_W + 165888, K3_SMEM = K3_BAR + 256 + 1024;

__global__ void __launch_bounds__(288, 1) k3_out(const __grid_constant__ CUtensorMap tmO, const __nv_bfloat16* __restrict__ woA,
                                                 const __nv_bfloat16* __restrict__ woB, __nv_bfloat16* __restrict__ out) {
  extern __shared__ uint8_t smem_raw[];
  const uint32_t sb = (smem_u32(smem_raw) + 1023) & ~1023u;
  const uint32_t afull = sb + K3_BAR, aempty = afull + 24;
  const int tid = threadIdx.x, warp = __shfl_sync(~0u, tid >> 5, 0), lane = tid & 31;
  const int rt = blockIdx.x >> 3, ct = blockIdx.x & 7;
  if (tid == 0) {
    for (int i = 0; i < 3; i++) { mbar_init(afull + 8 * i, 1); mbar_init(aempty + 8 * i, 8); }
    asm volatile("fence.mbarrier_init.release.cluster;" ::: "memory");
  }
  __syncthreads();
  if (warp == 8) {
    pdl_wait();
    if (lane == 0) {
      for (int kb = 0; kb < 18; kb++) {
        const int s = kb % 3;
        if (kb >= 3) mbar_wait(aempty + 8 * s, (kb / 3 - 1) & 1);
        mbar_expect(afull + 8 * s, 16384);
        tma2d(sb + K3_A + s * 16384, &tmO, kb * 64, rt * 128, afull + 8 * s);
      }
    }
  } else {
    for (int c = tid; c < 1152 * 9; c += 256) {
      const int kr = c & 7, q = c >> 3, kg = q / 9, nc = q - kg * 9, k = kg * 8 + kr;
      const __nv_bfloat16* src = (k < DM ? woA + k * DM : woB + (k - DM) * DM) + ct * 72 + nc * 8;
      asm volatile("cp.async.cg.shared.global [%0], [%1], 16;" :: "r"(sb + K3_W + c * 16), "l"(src) : "memory");
    }
    asm volatile("cp.async.wait_all;" ::: "memory");
    fence_async();
    asm volatile("bar.sync 1, 256;" ::: "memory");
    const int wg = warp >> 2, wq = warp & 3;
    float acc[36];
    const uint64_t dA = mkdesc(sb + K3_A + wg * 8192, 16, 1024, 1), dW = mkdesc(sb + K3_W, 1152, 128, 0);
    int s = 0, ph = 0;
#pragma unroll 1
    for (int kb = 0; kb < 18; kb++) {
      mbar_wait(afull + 8 * s, ph);
      const uint64_t da = dA + (uint64_t)(s * 1024), db = dW + (uint64_t)(kb * 576);
      wg_fence();
      wgmma_ss_n72_mn(acc, da, db, kb);
      wgmma_ss_n72_mn(acc, da + 2, db + 144, 1);
      wgmma_ss_n72_mn(acc, da + 4, db + 288, 1);
      wgmma_ss_n72_mn(acc, da + 6, db + 432, 1);
      wg_commit();
      wg_wait<0>();
      if (lane == 0) mbar_arrive(aempty + 8 * s);
      if (++s == 3) { s = 0; ph ^= 1; }
    }
    pin(acc);
    const int r0 = rt * 128 + wg * 64 + wq * 16 + (lane >> 2);
    uint32_t* p0 = (uint32_t*)(out + r0 * DM + ct * 72) + (lane & 3);
    uint32_t* p1 = p0 + 4 * DM;
#pragma unroll
    for (int b = 0; b < 9; b++) { p0[4 * b] = pack_bf16(acc[4 * b], acc[4 * b + 1]); p1[4 * b] = pack_bf16(acc[4 * b + 2], acc[4 * b + 3]); }
  }
}

typedef CUresult (*EncodeFn)(CUtensorMap*, CUtensorMapDataType, cuuint32_t, void*, const cuuint64_t*, const cuuint64_t*, const cuuint32_t*,
                             const cuuint32_t*, CUtensorMapInterleave, CUtensorMapSwizzle, CUtensorMapL2promotion, CUtensorMapFloatOOBfill);
static void make_map(EncodeFn fn, CUtensorMap* tm, void* ptr, uint64_t cols, uint64_t rows, uint32_t bc, uint32_t br) {
  cuuint64_t dims[2] = {cols, rows}, strides[1] = {cols * 2};
  cuuint32_t box[2] = {bc, br}, es[2] = {1, 1};
  fn(tm, CU_TENSOR_MAP_DATA_TYPE_BFLOAT16, 2, ptr, dims, strides, box, es, CU_TENSOR_MAP_INTERLEAVE_NONE, CU_TENSOR_MAP_SWIZZLE_128B,
     CU_TENSOR_MAP_L2_PROMOTION_L2_256B, CU_TENSOR_MAP_FLOAT_OOB_FILL_NONE);
}
template<class... A> static void launch(void (*k)(A...), int grid, int block, int smem, bool pdl, A... args) {
  cudaLaunchConfig_t cfg = {};
  cfg.gridDim = dim3(grid); cfg.blockDim = dim3(block); cfg.dynamicSmemBytes = smem; cfg.stream = cudaStreamPerThread;
  cudaLaunchAttribute at[1];
  at[0].id = cudaLaunchAttributeProgrammaticStreamSerialization; at[0].val.programmaticStreamSerializationAllowed = 1;
  cfg.attrs = at; cfg.numAttrs = pdl ? 1 : 0;
  cudaLaunchKernelEx(&cfg, k, args...);
}

extern "C" void kernel_launch(void* const* d_in, const int* in_sizes, int n_in, void* d_out, int out_size) {
  const __nv_bfloat16* x = (const __nv_bfloat16*)d_in[0];
  static CUtensorMap tmX, tmWA, tmWB, tmO;
  static bool init = false;
  if (!init) {
    void* fp = nullptr; cudaDriverEntryPointQueryResult qr;
    cudaGetDriverEntryPoint("cuTensorMapEncodeTiled", &fp, cudaEnableDefault, &qr);
    EncodeFn fn = (EncodeFn)fp;
    void* po = nullptr; cudaGetSymbolAddress(&po, g_o);
    make_map(fn, &tmX, d_in[0], DM, SEQ, 64, 128);
    make_map(fn, &tmWA, d_in[1], N3, DM, 64, 32);
    make_map(fn, &tmWB, d_in[4], N3, DM, 64, 32);
    make_map(fn, &tmO, po, 2 * DM, SEQ, 64, 128);
    cudaFuncSetAttribute(k1_qkv, cudaFuncAttributeMaxDynamicSharedMemorySize, K1_SMEM);
    cudaFuncSetAttribute(k2_attn, cudaFuncAttributeMaxDynamicSharedMemorySize, K2_SMEM);
    cudaFuncSetAttribute(k3_out, cudaFuncAttributeMaxDynamicSharedMemorySize, K3_SMEM);
    init = true;
  }
  launch(k1_qkv, 128, 384, K1_SMEM, false, tmX, tmWA, tmWB, x, (const __nv_bfloat16*)d_in[6]);
  launch(k2_attn, 128, 384, K2_SMEM, true);
  launch(k3_out, 128, 288, K3_SMEM, true, tmO, (const __nv_bfloat16*)d_in[2], (const __nv_bfloat16*)d_in[5], (__nv_bfloat16*)d_out);
}
```

```cpp
#include <cuda_runtime.h>
#include <cuda_bf16.h>
#include <cuda.h>
#include <stdint.h>

constexpr int SEQ = 2048, DM = 576, DH = 18, N3 = 1728;
constexpr int GRP = 384;
constexpr int IMG_PITCH = 192 * GRP;
constexpr int NVG = 260;
constexpr float QSCALE = 0.23570226039551584f * 1.4426950408889634f;
constexpr uint32_t POLY_MASK = 0x5F;

__device__ __align__(1024) uint8_t g_img[256 * IMG_PITCH];
__device__ __align__(1024) uint32_t g_gate[SEQ];
__device__ __align__(1024) uint4 g_o[144 * NVG * 8];
__device__ __align__(128) uint32_t g_cnt[128];
__device__ __align__(128) uint32_t g_flag[128];
__device__ uint32_t g_epoch[128];
__device__ uint64_t g_nrm[128];

__device__ __forceinline__ uint32_t smem_u32(const void* p) { return (uint32_t)__cvta_generic_to_shared(p); }
__device__ __forceinline__ void mbar_init(uint32_t bar, int cnt) { asm volatile("mbarrier.init.shared::cta.b64 [%0], %1;" :: "r"(bar), "r"(cnt)); }
__device__ __forceinline__ void mbar_expect(uint32_t bar, uint32_t bytes) { asm volatile("mbarrier.arrive.expect_tx.shared::cta.b64 _, [%0], %1;" :: "r"(bar), "r"(bytes) : "memory"); }
__device__ __forceinline__ void mbar_arrive(uint32_t bar) { asm volatile("mbarrier.arrive.shared::cta.b64 _, [%0];" :: "r"(bar) : "memory"); }
__device__ __forceinline__ void mbar_wait(uint32_t bar, uint32_t par) {
  uint32_t ok; int it = 0;
  do { asm volatile("{\n.reg .pred p;\nmbarrier.try_wait.parity.shared::cta.b64 p, [%1], %2;\nselp.u32 %0, 1, 0, p;\n}" : "=r"(ok) : "r"(bar), "r"(par) : "memory");
  } while (!ok && ++it < (1 << 22));
}
__device__ __forceinline__ uint32_t mbar_test(uint32_t bar, uint32_t par) {
  uint32_t ok;
  asm volatile("{\n.reg .pred p;\nmbarrier.test_wait.parity.shared::cta.b64 p, [%1], %2;\nselp.u32 %0, 1, 0, p;\n}" : "=r"(ok) : "r"(bar), "r"(par) : "memory");
  return ok;
}
__device__ __forceinline__ void mbar_sleep(uint32_t bar, uint32_t par) {
  uint32_t ok; int it = 0;
  do { asm volatile("{\n.reg .pred p;\nmbarrier.try_wait.parity.shared::cta.b64 p, [%1], %2, %3;\nselp.u32 %0, 1, 0, p;\n}" : "=r"(ok) : "r"(bar), "r"(par), "r"(20000) : "memory");
  } while (!ok && ++it < (1 << 16));
}
__device__ __forceinline__ void bulk_g2s(uint32_t dst, const void* src, uint32_t bytes, uint32_t bar) {
  asm volatile("cp.async.bulk.shared::cluster.global.mbarrier::complete_tx::bytes [%0], [%1], %2, [%3];" :: "r"(dst), "l"(src), "r"(bytes), "r"(bar) : "memory");
}
__device__ __forceinline__ void bulk_s2g(void* dst, uint32_t src, uint32_t bytes) {
  asm volatile("cp.async.bulk.global.shared::cta.bulk_group [%0], [%1], %2;" :: "l"(dst), "r"(src), "r"(bytes) : "memory");
}
__device__ __forceinline__ void tma2d(uint32_t dst, const CUtensorMap* tm, int c0, int c1, uint32_t bar) {
  asm volatile("cp.async.bulk.tensor.2d.shared::cluster.global.mbarrier::complete_tx::bytes [%0], [%1, {%3, %4}], [%2];"
               :: "r"(dst), "l"(tm), "r"(bar), "r"(c0), "r"(c1) : "memory");
}
__device__ __forceinline__ void l2_prefetch(const void* p, uint32_t bytes) { asm volatile("cp.async.bulk.prefetch.L2.global [%0], %1;" :: "l"(p), "r"(bytes) : "memory"); }
__device__ __forceinline__ void tm_prefetch(const CUtensorMap* tm) { asm volatile("prefetch.tensormap [%0];" :: "l"(tm) : "memory"); }
__device__ __forceinline__ bool elect_one() {
  uint32_t pred;
  asm volatile("{\n.reg .pred P;\nelect.sync _|P, 0xffffffff;\nselp.b32 %0, 1, 0, P;\n}" : "=r"(pred));
  return pred;
}
__device__ __forceinline__ void fence_async() { asm volatile("fence.proxy.async.shared::cta;" ::: "memory"); }
__device__ __forceinline__ void fence_async_global() { asm volatile("fence.proxy.async.global;" ::: "memory"); }
__device__ __forceinline__ void wg_fence() { asm volatile("wgmma.fence.sync.aligned;" ::: "memory"); }
__device__ __forceinline__ void wg_commit() { asm volatile("wgmma.commit_group.sync.aligned;" ::: "memory"); }
template<int N> __device__ __forceinline__ void wg_wait() { asm volatile("wgmma.wait_group.sync.aligned %0;" :: "n"(N) : "memory"); }
__device__ __forceinline__ uint64_t mkdesc(uint32_t addr, uint32_t lbo, uint32_t sbo, uint32_t swz) {
  uint64_t d = (uint64_t)((addr & 0x3FFFF) >> 4) | ((uint64_t)(lbo >> 4) << 16) | ((uint64_t)(sbo >> 4) << 32) | ((uint64_t)swz << 62);
  asm volatile("" : "+l"(d));
  return d;
}
template<int N> __device__ __forceinline__ void pin(float (&r)[N]) {
#pragma unroll
  for (int i = 0; i < N; i++) asm volatile("" : "+f"(r[i]) :: "memory");
}
template<int N> __device__ __forceinline__ void pin(uint32_t (&r)[N]) {
#pragma unroll
  for (int i = 0; i < N; i++) asm volatile("" : "+r"(r[i]) :: "memory");
}
__device__ __forceinline__ float ex2(float x) { float y; asm("ex2.approx.ftz.f32 %0, %1;" : "=f"(y) : "f"(x)); return y; }
__device__ __forceinline__ uint32_t pack_bf16(float lo, float hi) { uint32_t r; asm("cvt.rn.bf16x2.f32 %0, %1, %2;" : "=r"(r) : "f"(hi), "f"(lo)); return r; }
__device__ __forceinline__ uint32_t hfma2(uint32_t a, uint32_t b, uint32_t c) { uint32_t r; asm("fma.rn.bf16x2 %0, %1, %2, %3;" : "=r"(r) : "r"(a), "r"(b), "r"(c)); return r; }
__device__ __forceinline__ uint32_t hmul2(uint32_t a, uint32_t b) { uint32_t r; asm("mul.rn.bf16x2 %0, %1, %2;" : "=r"(r) : "r"(a), "r"(b)); return r; }
__device__ __forceinline__ float bf_lo(uint32_t v) { return __uint_as_float(v << 16); }
__device__ __forceinline__ float bf_hi(uint32_t v) { return __uint_as_float(v & 0xFFFF0000u); }
__device__ __forceinline__ float bf_round(float x) { return __bfloat162float(__float2bfloat16(x)); }
__device__ __forceinline__ void sts32(uint32_t a, uint32_t v) { asm volatile("st.shared.u32 [%0], %1;" :: "r"(a), "r"(v) : "memory"); }
__device__ __forceinline__ void sts128(uint32_t a, uint32_t v0, uint32_t v1, uint32_t v2, uint32_t v3) { asm volatile("st.shared.v4.u32 [%0], {%1, %2, %3, %4};" :: "r"(a), "r"(v0), "r"(v1), "r"(v2), "r"(v3) : "memory"); }
__device__ __forceinline__ void sts64(uint32_t a, uint32_t v0, uint32_t v1) { asm volatile("st.shared.v2.u32 [%0], {%1, %2};" :: "r"(a), "r"(v0), "r"(v1) : "memory"); }
__device__ __forceinline__ void tma3d(uint32_t dst, const CUtensorMap* tm, int c0, int c1, int c2, uint32_t bar) {
  asm volatile("cp.async.bulk.tensor.3d.shared::cluster.global.mbarrier::complete_tx::bytes [%0], [%1, {%3, %4, %5}], [%2];"
               :: "r"(dst), "l"(tm), "r"(bar), "r"(c0), "r"(c1), "r"(c2) : "memory");
}
__device__ __forceinline__ void tma2d_store(const CUtensorMap* tm, uint32_t src, int c0, int c1) {
  asm volatile("cp.async.bulk.tensor.2d.global.shared::cta.bulk_group [%0, {%2, %3}], [%1];" :: "l"(tm), "r"(src), "r"(c0), "r"(c1) : "memory");
}
__device__ __forceinline__ void bulk_commit() { asm volatile("cp.async.bulk.commit_group;" ::: "memory"); }
__device__ __forceinline__ void bulk_wait_read() { asm volatile("cp.async.bulk.wait_group.read 0;" ::: "memory"); }
__device__ __forceinline__ void bulk_wait_all() { asm volatile("cp.async.bulk.wait_group 0;" ::: "memory"); }
__device__ __forceinline__ void named_sync(int id, int n) { asm volatile("bar.sync %0, %1;" :: "r"(id), "r"(n) : "memory"); }
__device__ __forceinline__ void stsm4t(uint32_t a, uint32_t r0, uint32_t r1, uint32_t r2, uint32_t r3) {
  asm volatile("stmatrix.sync.aligned.m8n8.x4.trans.shared.b16 [%0], {%1,%2,%3,%4};" :: "r"(a), "r"(r0), "r"(r1), "r"(r2), "r"(r3) : "memory");
}
__device__ __forceinline__ uint32_t lds32(uint32_t a) { uint32_t v; asm volatile("ld.shared.u32 %0, [%1];" : "=r"(v) : "r"(a) : "memory"); return v; }
__device__ __forceinline__ void red_add(uint32_t* c) { asm volatile("red.relaxed.gpu.global.add.u32 [%0], 1;" :: "l"(c) : "memory"); }
__device__ __forceinline__ void signal(uint32_t* c) { asm volatile("fence.acq_rel.gpu;" ::: "memory"); red_add(c); }
__device__ __forceinline__ void await(const uint32_t* c, uint32_t target) {
  uint32_t v; int it = 0;
  do { asm volatile("ld.acquire.gpu.global.u32 %0, [%1];" : "=r"(v) : "l"(c) : "memory"); } while (__any_sync(~0u, (int)(v - target) < 0) && ++it < (1 << 20));
  fence_async_global();
}
__device__ __forceinline__ void await2(const uint32_t* c0, const uint32_t* c1, uint32_t target) { await((threadIdx.x & 1) ? c1 : c0, target); }
__device__ __forceinline__ float rcp(float x) { float y; asm("rcp.approx.ftz.f32 %0, %1;" : "=f"(y) : "f"(x)); return y; }
__device__ __forceinline__ void wgmma_ss_n256_mn(float (&d)[128], uint64_t descA, uint64_t descB, int scaleD) {
  asm volatile("{\n.reg .pred p;\nsetp.ne.b32 p, %130, 0;\n"
    "wgmma.mma_async.sync.aligned.m64n256k16.f32.bf16.bf16 {%0, %1, %2, %3, %4, %5, %6, %7, %8, %9, %10, %11, %12, %13, %14, %15, %16, %17, %18, %19, %20, %21, %22, %23, %24, %25, %26, %27, %28, %29, %30, %31, %32, %33, %34, %35, %36, %37, %38, %39, %40, %41, %42, %43, %44, %45, %46, %47, %48, %49, %50, %51, %52, %53, %54, %55, %56, %57, %58, %59, %60, %61, %62, %63, %64, %65, %66, %67, %68, %69, %70, %71, %72, %73, %74, %75, %76, %77, %78, %79, %80, %81, %82, %83, %84, %85, %86, %87, %88, %89, %90, %91, %92, %93, %94, %95, %96, %97, %98, %99, %100, %101, %102, %103, %104, %105, %106, %107, %108, %109, %110, %111, %112, %113, %114, %115, %116, %117, %118, %119, %120, %121, %122, %123, %124, %125, %126, %127}, %128, %129, p, 1, 1, 0, 1;\n}\n"
    : "+f"(d[0]), "+f"(d[1]), "+f"(d[2]), "+f"(d[3]), "+f"(d[4]), "+f"(d[5]), "+f"(d[6]), "+f"(d[7]), "+f"(d[8]), "+f"(d[9]), "+f"(d[10]), "+f"(d[11]), "+f"(d[12]), "+f"(d[13]), "+f"(d[14]), "+f"(d[15]), "+f"(d[16]), "+f"(d[17]), "+f"(d[18]), "+f"(d[19]), "+f"(d[20]), "+f"(d[21]), "+f"(d[22]), "+f"(d[23]), "+f"(d[24]), "+f"(d[25]), "+f"(d[26]), "+f"(d[27]), "+f"(d[28]), "+f"(d[29]), "+f"(d[30]), "+f"(d[31]), "+f"(d[32]), "+f"(d[33]), "+f"(d[34]), "+f"(d[35]), "+f"(d[36]), "+f"(d[37]), "+f"(d[38]), "+f"(d[39]), "+f"(d[40]), "+f"(d[41]), "+f"(d[42]), "+f"(d[43]), "+f"(d[44]), "+f"(d[45]), "+f"(d[46]), "+f"(d[47]), "+f"(d[48]), "+f"(d[49]), "+f"(d[50]), "+f"(d[51]), "+f"(d[52]), "+f"(d[53]), "+f"(d[54]), "+f"(d[55]), "+f"(d[56]), "+f"(d[57]), "+f"(d[58]), "+f"(d[59]), "+f"(d[60]), "+f"(d[61]), "+f"(d[62]), "+f"(d[63]), "+f"(d[64]), "+f"(d[65]), "+f"(d[66]), "+f"(d[67]), "+f"(d[68]), "+f"(d[69]), "+f"(d[70]), "+f"(d[71]), "+f"(d[72]), "+f"(d[73]), "+f"(d[74]), "+f"(d[75]), "+f"(d[76]), "+f"(d[77]), "+f"(d[78]), "+f"(d[79]), "+f"(d[80]), "+f"(d[81]), "+f"(d[82]), "+f"(d[83]), "+f"(d[84]), "+f"(d[85]), "+f"(d[86]), "+f"(d[87]), "+f"(d[88]), "+f"(d[89]), "+f"(d[90]), "+f"(d[91]), "+f"(d[92]), "+f"(d[93]), "+f"(d[94]), "+f"(d[95]), "+f"(d[96]), "+f"(d[97]), "+f"(d[98]), "+f"(d[99]), "+f"(d[100]), "+f"(d[101]), "+f"(d[102]), "+f"(d[103]), "+f"(d[104]), "+f"(d[105]), "+f"(d[106]), "+f"(d[107]), "+f"(d[108]), "+f"(d[109]), "+f"(d[110]), "+f"(d[111]), "+f"(d[112]), "+f"(d[113]), "+f"(d[114]), "+f"(d[115]), "+f"(d[116]), "+f"(d[117]), "+f"(d[118]), "+f"(d[119]), "+f"(d[120]), "+f"(d[121]), "+f"(d[122]), "+f"(d[123]), "+f"(d[124]), "+f"(d[125]), "+f"(d[126]), "+f"(d[127])
    : "l"(descA), "l"(descB), "r"(scaleD));
}

__device__ __forceinline__ void wgmma_ss_n192_mn(float (&d)[96], uint64_t descA, uint64_t descB, int scaleD) {
  asm volatile("{\n.reg .pred p;\nsetp.ne.b32 p, %98, 0;\n"
    "wgmma.mma_async.sync.aligned.m64n192k16.f32.bf16.bf16 {%0, %1, %2, %3, %4, %5, %6, %7, %8, %9, %10, %11, %12, %13, %14, %15, %16, %17, %18, %19, %20, %21, %22, %23, %24, %25, %26, %27, %28, %29, %30, %31, %32, %33, %34, %35, %36, %37, %38, %39, %40, %41, %42, %43, %44, %45, %46, %47, %48, %49, %50, %51, %52, %53, %54, %55, %56, %57, %58, %59, %60, %61, %62, %63, %64, %65, %66, %67, %68, %69, %70, %71, %72, %73, %74, %75, %76, %77, %78, %79, %80, %81, %82, %83, %84, %85, %86, %87, %88, %89, %90, %91, %92, %93, %94, %95}, %96, %97, p, 1, 1, 0, 1;\n}\n"
    : "+f"(d[0]), "+f"(d[1]), "+f"(d[2]), "+f"(d[3]), "+f"(d[4]), "+f"(d[5]), "+f"(d[6]), "+f"(d[7]), "+f"(d[8]), "+f"(d[9]), "+f"(d[10]), "+f"(d[11]), "+f"(d[12]), "+f"(d[13]), "+f"(d[14]), "+f"(d[15]), "+f"(d[16]), "+f"(d[17]), "+f"(d[18]), "+f"(d[19]), "+f"(d[20]), "+f"(d[21]), "+f"(d[22]), "+f"(d[23]), "+f"(d[24]), "+f"(d[25]), "+f"(d[26]), "+f"(d[27]), "+f"(d[28]), "+f"(d[29]), "+f"(d[30]), "+f"(d[31]), "+f"(d[32]), "+f"(d[33]), "+f"(d[34]), "+f"(d[35]), "+f"(d[36]), "+f"(d[37]), "+f"(d[38]), "+f"(d[39]), "+f"(d[40]), "+f"(d[41]), "+f"(d[42]), "+f"(d[43]), "+f"(d[44]), "+f"(d[45]), "+f"(d[46]), "+f"(d[47]), "+f"(d[48]), "+f"(d[49]), "+f"(d[50]), "+f"(d[51]), "+f"(d[52]), "+f"(d[53]), "+f"(d[54]), "+f"(d[55]), "+f"(d[56]), "+f"(d[57]), "+f"(d[58]), "+f"(d[59]), "+f"(d[60]), "+f"(d[61]), "+f"(d[62]), "+f"(d[63]), "+f"(d[64]), "+f"(d[65]), "+f"(d[66]), "+f"(d[67]), "+f"(d[68]), "+f"(d[69]), "+f"(d[70]), "+f"(d[71]), "+f"(d[72]), "+f"(d[73]), "+f"(d[74]), "+f"(d[75]), "+f"(d[76]), "+f"(d[77]), "+f"(d[78]), "+f"(d[79]), "+f"(d[80]), "+f"(d[81]), "+f"(d[82]), "+f"(d[83]), "+f"(d[84]), "+f"(d[85]), "+f"(d[86]), "+f"(d[87]), "+f"(d[88]), "+f"(d[89]), "+f"(d[90]), "+f"(d[91]), "+f"(d[92]), "+f"(d[93]), "+f"(d[94]), "+f"(d[95])
    : "l"(descA), "l"(descB), "r"(scaleD));
}

__device__ __forceinline__ void wgmma_st_n80_k(float (&d)[40], uint64_t descA, uint64_t descB) {
  asm volatile("{\n.reg .pred p;\nsetp.eq.b32 p, 0, 0;\n"
    "wgmma.mma_async.sync.aligned.m64n80k16.f32.bf16.bf16 {%0, %1, %2, %3, %4, %5, %6, %7, %8, %9, %10, %11, %12, %13, %14, %15, %16, %17, %18, %19, %20, %21, %22, %23, %24, %25, %26, %27, %28, %29, %30, %31, %32, %33, %34, %35, %36, %37, %38, %39}, %40, %41, p, 1, 1, 1, 0;\n}\n"
    : "+f"(d[0]), "+f"(d[1]), "+f"(d[2]), "+f"(d[3]), "+f"(d[4]), "+f"(d[5]), "+f"(d[6]), "+f"(d[7]), "+f"(d[8]), "+f"(d[9]), "+f"(d[10]), "+f"(d[11]), "+f"(d[12]), "+f"(d[13]), "+f"(d[14]), "+f"(d[15]), "+f"(d[16]), "+f"(d[17]), "+f"(d[18]), "+f"(d[19]), "+f"(d[20]), "+f"(d[21]), "+f"(d[22]), "+f"(d[23]), "+f"(d[24]), "+f"(d[25]), "+f"(d[26]), "+f"(d[27]), "+f"(d[28]), "+f"(d[29]), "+f"(d[30]), "+f"(d[31]), "+f"(d[32]), "+f"(d[33]), "+f"(d[34]), "+f"(d[35]), "+f"(d[36]), "+f"(d[37]), "+f"(d[38]), "+f"(d[39])
    : "l"(descA), "l"(descB));
}

template<int SD> __device__ __forceinline__ void wgmma_rs_n80_k(float (&d)[40], uint32_t a0, uint32_t a1, uint32_t a2, uint32_t a3, uint64_t descB) {
  asm volatile("{\n.reg .pred p;\nsetp.ne.b32 p, %45, 0;\n"
    "wgmma.mma_async.sync.aligned.m64n80k16.f32.bf16.bf16 {%0, %1, %2, %3, %4, %5, %6, %7, %8, %9, %10, %11, %12, %13, %14, %15, %16, %17, %18, %19, %20, %21, %22, %23, %24, %25, %26, %27, %28, %29, %30, %31, %32, %33, %34, %35, %36, %37, %38, %39}, {%40, %41, %42, %43}, %44, p, 1, 1, 0;\n}\n"
    : "+f"(d[0]), "+f"(d[1]), "+f"(d[2]), "+f"(d[3]), "+f"(d[4]), "+f"(d[5]), "+f"(d[6]), "+f"(d[7]), "+f"(d[8]), "+f"(d[9]), "+f"(d[10]), "+f"(d[11]), "+f"(d[12]), "+f"(d[13]), "+f"(d[14]), "+f"(d[15]), "+f"(d[16]), "+f"(d[17]), "+f"(d[18]), "+f"(d[19]), "+f"(d[20]), "+f"(d[21]), "+f"(d[22]), "+f"(d[23]), "+f"(d[24]), "+f"(d[25]), "+f"(d[26]), "+f"(d[27]), "+f"(d[28]), "+f"(d[29]), "+f"(d[30]), "+f"(d[31]), "+f"(d[32]), "+f"(d[33]), "+f"(d[34]), "+f"(d[35]), "+f"(d[36]), "+f"(d[37]), "+f"(d[38]), "+f"(d[39])
    : "r"(a0), "r"(a1), "r"(a2), "r"(a3), "l"(descB), "n"(SD));
}

__device__ __forceinline__ void wgmma_rs_n80_k0(float (&d)[40], uint32_t a0, uint32_t a1, uint32_t a2, uint32_t a3, uint64_t descB) {
  asm volatile("{\n.reg .pred p;\nsetp.ne.b32 p, 0, 0;\n"
    "wgmma.mma_async.sync.aligned.m64n80k16.f32.bf16.bf16 {%0, %1, %2, %3, %4, %5, %6, %7, %8, %9, %10, %11, %12, %13, %14, %15, %16, %17, %18, %19, %20, %21, %22, %23, %24, %25, %26, %27, %28, %29, %30, %31, %32, %33, %34, %35, %36, %37, %38, %39}, {%40, %41, %42, %43}, %44, p, 1, 1, 0;\n}\n"
    : "=f"(d[0]), "=f"(d[1]), "=f"(d[2]), "=f"(d[3]), "=f"(d[4]), "=f"(d[5]), "=f"(d[6]), "=f"(d[7]), "=f"(d[8]), "=f"(d[9]), "=f"(d[10]), "=f"(d[11]), "=f"(d[12]), "=f"(d[13]), "=f"(d[14]), "=f"(d[15]), "=f"(d[16]), "=f"(d[17]), "=f"(d[18]), "=f"(d[19]), "=f"(d[20]), "=f"(d[21]), "=f"(d[22]), "=f"(d[23]), "=f"(d[24]), "=f"(d[25]), "=f"(d[26]), "=f"(d[27]), "=f"(d[28]), "=f"(d[29]), "=f"(d[30]), "=f"(d[31]), "=f"(d[32]), "=f"(d[33]), "=f"(d[34]), "=f"(d[35]), "=f"(d[36]), "=f"(d[37]), "=f"(d[38]), "=f"(d[39])
    : "r"(a0), "r"(a1), "r"(a2), "r"(a3), "l"(descB));
}

__device__ __forceinline__ void wgmma_rs_n24_mn0(float (&d)[12], uint32_t a0, uint32_t a1, uint32_t a2, uint32_t a3, uint64_t descB) {
  asm volatile("{\n.reg .pred p;\nsetp.ne.b32 p, 0, 0;\n"
    "wgmma.mma_async.sync.aligned.m64n24k16.f32.bf16.bf16 {%0, %1, %2, %3, %4, %5, %6, %7, %8, %9, %10, %11}, {%12, %13, %14, %15}, %16, p, 1, 1, 1;\n}\n"
    : "=f"(d[0]), "=f"(d[1]), "=f"(d[2]), "=f"(d[3]), "=f"(d[4]), "=f"(d[5]), "=f"(d[6]), "=f"(d[7]), "=f"(d[8]), "=f"(d[9]), "=f"(d[10]), "=f"(d[11])
    : "r"(a0), "r"(a1), "r"(a2), "r"(a3), "l"(descB));
}

template<int SD> __device__ __forceinline__ void wgmma_rs_n64_k(float (&d)[32], uint32_t a0, uint32_t a1, uint32_t a2, uint32_t a3, uint64_t descB) {
  asm volatile("{\n.reg .pred p;\nsetp.ne.b32 p, %37, 0;\n"
    "wgmma.mma_async.sync.aligned.m64n64k16.f32.bf16.bf16 {%0, %1, %2, %3, %4, %5, %6, %7, %8, %9, %10, %11, %12, %13, %14, %15, %16, %17, %18, %19, %20, %21, %22, %23, %24, %25, %26, %27, %28, %29, %30, %31}, {%32, %33, %34, %35}, %36, p, 1, 1, 0;\n}\n"
    : "+f"(d[0]), "+f"(d[1]), "+f"(d[2]), "+f"(d[3]), "+f"(d[4]), "+f"(d[5]), "+f"(d[6]), "+f"(d[7]), "+f"(d[8]), "+f"(d[9]), "+f"(d[10]), "+f"(d[11]), "+f"(d[12]), "+f"(d[13]), "+f"(d[14]), "+f"(d[15]), "+f"(d[16]), "+f"(d[17]), "+f"(d[18]), "+f"(d[19]), "+f"(d[20]), "+f"(d[21]), "+f"(d[22]), "+f"(d[23]), "+f"(d[24]), "+f"(d[25]), "+f"(d[26]), "+f"(d[27]), "+f"(d[28]), "+f"(d[29]), "+f"(d[30]), "+f"(d[31])
    : "r"(a0), "r"(a1), "r"(a2), "r"(a3), "l"(descB), "n"(SD));
}

template<int SD> __device__ __forceinline__ void wgmma_rs_n24_mn(float (&d)[12], uint32_t a0, uint32_t a1, uint32_t a2, uint32_t a3, uint64_t descB) {
  asm volatile("{\n.reg .pred p;\nsetp.ne.b32 p, %17, 0;\n"
    "wgmma.mma_async.sync.aligned.m64n24k16.f32.bf16.bf16 {%0, %1, %2, %3, %4, %5, %6, %7, %8, %9, %10, %11}, {%12, %13, %14, %15}, %16, p, 1, 1, 1;\n}\n"
    : "+f"(d[0]), "+f"(d[1]), "+f"(d[2]), "+f"(d[3]), "+f"(d[4]), "+f"(d[5]), "+f"(d[6]), "+f"(d[7]), "+f"(d[8]), "+f"(d[9]), "+f"(d[10]), "+f"(d[11])
    : "r"(a0), "r"(a1), "r"(a2), "r"(a3), "l"(descB), "n"(SD));
}


constexpr int SM_X = 0, SM_W = 147456, SM_SPARE = 212992;
constexpr int SM_KV = 0, KVST = 24576;
constexpr int SM_L = 196608, LBUF = 20 * GRP, SM_Q = 216064, SM_G = 228352, SM_M = SM_G + 2048;
constexpr int SM_O = 3 * KVST, OBLK = 20480;
constexpr int SM_BAR = SM_M + 1024, SMEM_BYTES = SM_BAR + 1024;
enum { B_X = 0, B_WF = 9, B_WE = 14, B_P = 19, B_QR = 26, B_J0 = 27, B_SF = 28, B_K0 = 36, B_KV = 37, B_CK = 45, B_Q2 = 46,
       B_F = 47, B_L = 49, B_WO = 50, B_OF = 56, B_W2F = 75, B_W2E = 79, B_FR = 83, B_S2 = 87, B_COUNT = 89 };
enum { C_T1 = 0, C_T2 = 32, C_LOC = 64, C_EARLY = 96 };

struct Maps { CUtensorMap x, wA, wB, img32, img10, o20, o10, o10h, woMainA, woTailA, woMainB, woTailB, out; };

__device__ __forceinline__ int cm_of(int p) { const int s = p / 9; return s * 3 + ((p - 9 * s) >> 2); }
template<int U> __device__ __forceinline__ void piece_stage(const uint32_t (&pk)[48], const uint32_t (&off)[9], uint32_t stg, uint32_t shift,
                                                            uint32_t c1, uint32_t c2, int lane) {
  constexpr int q = U % 3, rh = U / 3;
  const uint32_t base = stg - shift;
  const uint32_t a = stg + (lane >> 3) * GRP + 256 + (lane & 7) * 16;
  sts128(a, 0, c1, c2, 0);
  if (lane < 8) sts128(a + 4 * GRP, 0, c1, c2, 0);
  __syncwarp();
#pragma unroll
  for (int j = q ? 8 * q - 1 : 0; j < 8 * q + 8; j++) sts32(base + off[j % 9] + (j / 9) * 4 * GRP, pk[2 * j + rh]);
}
__device__ __forceinline__ void piece_hand(int u, uint32_t bars, int lane) {
  fence_async();
  __syncwarp();
  if (lane == 0) mbar_arrive(bars + 8 * (B_P + u));
}
__device__ __forceinline__ uint32_t piece_buf(uint32_t sb, int u, int w) {
  return sb + ((u == 0 || u == 2) ? SM_SPARE + w * 1920 : SM_X + ((u == 3 || u == 4) ? u - 2 : 0) * 16384 + w * 2048);
}
__device__ __forceinline__ void edge_store(uint32_t v0, uint32_t v1, uint32_t off, int slice0, int grp) {
  uint8_t* p = g_img + (size_t)grp * IMG_PITCH + slice0 * GRP + off;
  *(uint32_t*)p = v0; *(uint32_t*)(p + IMG_PITCH) = v1;
}
template<int N> __device__ __forceinline__ void pack_acc(uint32_t (&pk)[N], const float (&acc)[2 * N]) {
#pragma unroll
  for (int i = 0; i < N; i++) pk[i] = pack_bf16(acc[2 * i], acc[2 * i + 1]);
}
__device__ __forceinline__ void make_off(uint32_t (&off)[9], int phi, uint32_t base, int lane) {
#pragma unroll
  for (int j = 0; j < 9; j++) {
    const uint32_t p = phi + 4 * j + (lane & 3), hh = (p * 57) >> 9, r9 = p - 9 * hh;
    off[j] = hh * GRP + (r9 >> 2) * 128 + (r9 & 3) * 4 + (lane >> 2) * 16 + base;
  }
}
__device__ __forceinline__ void load_x(const Maps& mp, uint32_t sb, int kb, int rt) {
  const uint32_t bar = sb + SM_BAR + 8 * (B_X + kb);
  mbar_expect(bar, 16384);
  tma2d(sb + SM_X + kb * 16384, &mp.x, kb * 64, rt * 128, bar);
}
__device__ __forceinline__ void load_w1(const Maps& mp, uint32_t sb, int it, int s, int col) {
  const uint32_t bar = sb + SM_BAR + 8 * (B_WF + s);
  mbar_expect(bar, 12288);
#pragma unroll
  for (int a = 0; a < 3; a++) tma2d(sb + SM_W + (s ? s - 1 : 4) * 12288 + a * 4096, &mp.wA, col + a * 64, it * 32, bar);
}
template<int IT> __device__ __forceinline__ void proj2_step(float (&acc)[128], uint64_t dX, uint64_t dW, uint32_t bars) {
  mbar_wait(bars + 8 * (B_W2F + (IT & 3)), (IT >> 2) & 1);
  const uint64_t da = dX + (IT >> 1) * 1024 + (IT & 1) * 4, db = dW + ((IT + 2) & 3) * 1024;
  wg_fence();
  wgmma_ss_n256_mn(acc, da, db, IT); wgmma_ss_n256_mn(acc, da + 2, db + 128, 1);
  wg_commit();
}
template<int IT> __device__ __forceinline__ void proj2_done(uint32_t bars, int lane) {
  wg_wait<1>();
  if (IT > 0 && IT < 15 && lane == 0) mbar_arrive(bars + 8 * (B_W2E + ((IT - 1) & 3)));
}
__device__ __forceinline__ int slice_q(int band) { return (band & 1) ? 64 : 0; }
__device__ __forceinline__ int slice_k(int band) { return (band & 1) ? 0 : 32; }
__device__ __forceinline__ int slot_band(int s) { return (s & 4) + 2 * (s & 1) + ((s & 2) ? 0 : 1); }

__device__ __forceinline__ void softmax64(const float (&s)[32], uint32_t (&p)[16], uint32_t khalf, uint32_t k16) {
#pragma unroll
  for (int i = 0; i < 16; i++) {
    if ((POLY_MASK >> (i >> 1)) & 1) {
      uint32_t U, M;
      U = __float_as_uint(s[2 * i + 1]) * k16 + __float_as_uint(s[2 * i]);
      asm("lop3.b32 %0, %1, 0x007F007F, %2, 0xEA;" : "=r"(M) : "r"(U), "r"(khalf));
      p[i] = hfma2(M, U, U & 0xFF80FF80u);
    } else {
      p[i] = pack_bf16(ex2(s[2 * i]), ex2(s[2 * i + 1]));
    }
  }
}
__device__ __forceinline__ void issue_S(float (&s)[32], const uint32_t (&q)[8], uint64_t kd) {
  wgmma_rs_n64_k<0>(s, q[0], q[1], q[2], q[3], kd);
  wgmma_rs_n64_k<1>(s, q[4], q[5], q[6], q[7], kd + 16 - (8ull << 16));
}
__device__ __forceinline__ void issue_PV(float (&o)[12], const uint32_t (&p)[16], uint64_t vd) {
#pragma unroll
  for (int k = 0; k < 4; k++) wgmma_rs_n24_mn<1>(o, p[4 * k], p[4 * k + 1], p[4 * k + 2], p[4 * k + 3], vd + k * 48);
}
__device__ __forceinline__ void load_q_global(uint32_t (&q)[8], int h, int row0, int lane) {
  const uint32_t* p = (const uint32_t*)(g_img + (size_t)(row0 >> 3) * IMG_PITCH + h * GRP) + lane;
  const uint32_t* r = p + IMG_PITCH / 4;
  q[0] = __ldcg(p); q[1] = __ldcg(r); q[2] = __ldcg(p + 32); q[3] = __ldcg(r + 32);
  q[4] = __ldcg(p + 64); q[5] = __ldcg(r + 64); q[6] = 0; q[7] = 0;
}
__device__ __forceinline__ void load_q_shared(uint32_t (&q)[8], uint32_t a) {
  q[0] = lds32(a); q[1] = lds32(a + GRP); q[2] = lds32(a + 128); q[3] = lds32(a + GRP + 128);
  q[4] = lds32(a + 256); q[5] = lds32(a + GRP + 256);
  q[6] = lds32((a + 256) | 12); q[7] = lds32((a + GRP + 256) | 12);
}
__device__ __forceinline__ void scale_q(uint32_t (&q)[8], uint32_t ext, int lane) {
#pragma unroll
  for (int i = 0; i < 6; i++) q[i] = pack_bf16(bf_lo(q[i]) * QSCALE, bf_hi(q[i]) * QSCALE);
  if (lane & 3) { q[4] = ext; q[5] = ext; }
}
__device__ __forceinline__ uint32_t row_norm2_max(uint32_t m, const uint8_t* p) {
  const uint4 a = *(const uint4*)p, b = *(const uint4*)(p + 128); const uint32_t c = *(const uint32_t*)(p + 256);
  uint32_t u = hfma2(c, c, 0);
  u = hfma2(a.x, a.x, u); u = hfma2(a.y, a.y, u); u = hfma2(a.z, a.z, u); u = hfma2(a.w, a.w, u);
  u = hfma2(b.x, b.x, u); u = hfma2(b.y, b.y, u); u = hfma2(b.z, b.z, u); u = hfma2(b.w, b.w, u);
  asm("{\n.reg .b16 l, h;\n.reg .b32 w;\nmov.b32 {l, h}, %1;\nmov.b32 w, {h, l};\nadd.rn.bf16x2 w, w, %1;\nmax.NaN.bf16x2 %0, %0, w;\n}" : "+r"(m) : "r"(u));
  return m;
}
template<int BR, int N> __device__ __forceinline__ void store_o(const float (&o)[N][12], int rel0, int h, uint32_t sgate, int lane) {
  const uint32_t om = (BR * 72 + 2 * h) * (NVG * 128) + lane * 4, dt = (64 + (h >> 2) - 2 * h) * (NVG * 128) + (h & 3) * 4;
  const uint32_t ga = sgate + (rel0 + (lane >> 2)) * 4, wa = sgate + 2048 + (rel0 >> 1);
  float sc[N][2]; uint32_t w[N][2];
#pragma unroll
  for (int f = 0; f < N; f++)
#pragma unroll
    for (int r = 0; r < 2; r++) {
      const uint32_t g = lds32(ga + f * 256 + r * 32);
      sc[f][r] = (BR ? bf_hi(g) : bf_lo(g)) * rcp(__shfl_sync(~0u, o[f][8 + 2 * r], (lane & ~3) | 1));
      w[f][r] = om + lds32(wa + f * 32 + r * 4);
    }
#pragma unroll
  for (int f = 0; f < N; f++)
#pragma unroll
    for (int r = 0; r < 2; r++) {
      uint8_t* p = (uint8_t*)g_o + w[f][r];
      *(uint32_t*)p = pack_bf16(o[f][2 * r] * sc[f][r], o[f][2 * r + 1] * sc[f][r]);
      *(uint32_t*)(p + NVG * 128) = pack_bf16(o[f][4 + 2 * r] * sc[f][r], o[f][5 + 2 * r] * sc[f][r]);
      const uint32_t v = pack_bf16(o[f][8 + 2 * r] * sc[f][r], o[f][9 + 2 * r] * sc[f][r]);
      asm volatile("{\n.reg .pred q;\nsetp.eq.u32 q, %2, 0;\n@q st.global.u32 [%0], %1;\n}" :: "l"((uint8_t*)g_o + (w[f][r] + dt)), "r"(v), "r"(lane & 3) : "memory");
    }
}
template<int W> __device__ __forceinline__ void local_softmax(const float (&s)[40], uint32_t (&p)[20], int key0, int lane, uint3 sel) {
  const int g = lane >> 2, t2 = (lane & 3) * 2, par = g & 1;
  const bool lo = t2 > (g & ~1);
  const float NEG = __int_as_float(0xff800000);
#pragma unroll
  for (int r = 0; r < 2; r++) {
    const int b = 8 * W + 6 * r;
    float a = lo ? (par ? s[b + 1] : s[b]) : (par ? s[b + 9] : s[b + 8]), c = par ? s[b + 5] : s[b + 4];
    const int k = key0 + 16 * W + 8 * r + t2 + par;
    a = (k + (lo ? 0 : 16)) >= 0 ? a : NEG;
    c = (k + 8) >= 0 ? c : NEG;
    float m = fmaxf(a, c);
    m = fmaxf(m, __shfl_xor_sync(~0u, m, 1)); m = fmaxf(m, __shfl_xor_sync(~0u, m, 2));
    const uint32_t w = pack_bf16(ex2((a - m) * QSCALE), ex2((c - m) * QSCALE));
    p[4 * W + 3 * r] = __byte_perm(w, 0, sel.x); p[4 * W + 4 + 3 * r] = __byte_perm(w, 0, sel.y); p[4 * W + 2 + 3 * r] = __byte_perm(w, 0, sel.z);
  }
}
__device__ __forceinline__ void load_kv(const Maps& mp, uint32_t sb, int s, int h, bool first = false) {
  const uint32_t bar = sb + SM_BAR + 8 * (B_KV + s), kbar = first ? bar - 8 : bar;
  mbar_expect(kbar, KVST);
  const int band = slot_band(s), c = (slice_k(band) + h) * 192;
  tma2d(sb + SM_KV + s * KVST, &mp.img32, c, band * 32, kbar);
  if (first) { tma2d(sb + SM_Q, &mp.img32, h * 192, (blockIdx.x & 3) * 64, kbar); mbar_expect(bar, 12288); }
  tma2d(sb + SM_KV + s * KVST + 12288, &mp.img32, c + 32 * 192, band * 32, bar);
}
__device__ __forceinline__ void load_wo(const Maps& mp, uint32_t dst, int br, int j, int ft, uint32_t bar) {
  mbar_expect(bar, KVST);
  const CUtensorMap* mm = br ? &mp.woMainB : &mp.woMainA;
  tma3d(dst, mm, ft * 64, 0, j * 12, bar);
  tma3d(dst + 8192, mm, ft * 64, 0, j * 12 + 4, bar);
  if (j < 2) tma3d(dst + 16384, mm, ft * 64, 0, j * 12 + 8, bar);
  else tma3d(dst + 16384, br ? &mp.woTailB : &mp.woTailA, ft * 64, 16, 0, bar);
}
__device__ __forceinline__ constexpr int o_buf(int e) { constexpr int t[19] = {6, 0, 1, 2, 3, 4, 5, 6, 0, 1, 2, 3, 4, 7, 5, 6, 0, 1, 2}; return t[e]; }
template<int E> __device__ __forceinline__ void load_o(const Maps& mp, uint32_t sb, int tt) {
  constexpr int j = E < 14 ? E - 9 : E - 14;
  const uint32_t bar = sb + SM_BAR + 8 * (B_OF + E);
  constexpr bool half = E == 13 || E == 18;
  mbar_expect(bar, half ? OBLK / 2 : OBLK);
  tma3d(sb + SM_O + o_buf(E) * OBLK, E < 9 ? &mp.o20 : half ? &mp.o10h : &mp.o10, 0, tt * 20 + (E < 14 ? 0 : 10), E < 9 ? 72 + E * 8 : j * 16, bar);
}
template<int E> __device__ __forceinline__ void proj_b(float (&accE)[40], float (&accL)[40], uint64_t dA, uint64_t dB, uint32_t bars) {
  mbar_wait(bars + 8 * (B_OF + E), 0);
  const uint64_t da = dA + E * 512, db = dB + o_buf(E) * (OBLK / 16);
  wg_fence();
#pragma unroll
  for (int k = 0; k < 4; k++) { wgmma_st_n80_k(accE, da + k * 128, db + k * 320); wgmma_st_n80_k(accL, da + k * 128, db + k * 320 + 80); }
  wg_commit();
}
template<int E> __device__ __forceinline__ void proj_a(float (&acc)[40], uint64_t dA, uint64_t dB, uint32_t bars) {
  constexpr int j = E < 14 ? E - 9 : E - 14;
  mbar_wait(bars + 8 * (B_OF + E), 0);
  uint64_t da = dA + j * 1024;
  const uint64_t db = dB + o_buf(E) * (OBLK / 16);
  if (E >= 14 && E < 18) da = dA + (uint64_t)(__shfl_sync(~0u, lds32(bars - SM_BAR + SM_M + 336 + 4 * j), 0) * 1024);
  wg_fence();
#pragma unroll
  for (int k = 0; k < (j < 4 ? 8 : 4); k++) wgmma_st_n80_k(acc, da + k * 128, db + k * 160);
  wg_commit();
}
__device__ __forceinline__ void proj_store(const Maps& mp, const float (&a)[40], uint32_t ob, int part, int ft, int tt, int wq, int lane) {
  const int l8 = lane & 7, m4 = lane >> 3, ch = 2 * wq + (m4 & 1);
#pragma unroll
  for (int b = 0; b < 10; b += 2)
    stsm4t(ob + (8 * (b + (m4 >> 1)) + l8) * 128 + ((ch ^ l8) << 4), pack_bf16(a[4 * b], a[4 * b + 1]), pack_bf16(a[4 * b + 2], a[4 * b + 3]),
           pack_bf16(a[4 * b + 4], a[4 * b + 5]), pack_bf16(a[4 * b + 6], a[4 * b + 7]));
  fence_async();
  named_sync(3, 128);
  if (elect_one()) {
#pragma unroll
    for (int j = 0; j < 3; j++) {
      const int i = wq + 4 * j, e = tt * 10 + i;
      if (i < 10 && e < 128) tma2d_store(&mp.out, ob + i * 1024, ft * 64, ((e >> 5) * 64 + part * 32 + (e & 31)) * 8);
    }
    bulk_commit();
  }
}
__device__ __forceinline__ void load_local(const Maps& mp, uint32_t dst, uint32_t bar, int h, int row0) {
  mbar_expect(bar, 2 * LBUF);
#pragma unroll
  for (int i = 0; i < 4; i++) tma2d(dst + i * 10 * GRP, &mp.img10, (128 + 32 * (i & 1) + h) * 192, (row0 >> 3) + (i >> 1) * 8 - 2, bar);
}
__device__ __forceinline__ void local_pair(float (&o)[2][12], uint32_t (&q)[2][8], uint32_t (&p)[2][20], uint64_t kd, uint64_t vd, int row0,
                                           const uint32_t* qn, int wq, int lane, uint3 sel) {
  {
    float s[2][40];
    pin(q[0]); pin(q[1]);
    wg_fence();
#pragma unroll
    for (int f = 0; f < 2; f++) {
      wgmma_rs_n80_k0(s[f], q[f][0], q[f][1], q[f][2], q[f][3], kd + f * (LBUF / 16));
      wgmma_rs_n80_k<1>(s[f], q[f][4], q[f][5], q[f][6], q[f][7], kd + f * (LBUF / 16) + 16 - (8ull << 16));
    }
    wg_commit();
    wg_wait<0>(); pin(s[0]); pin(s[1]); pin(q[0]); pin(q[1]);
#pragma unroll
    for (int i = 0; i < 12; i++) q[i / 6][i % 6] = __ldcg(qn + (i / 6) * (2 * IMG_PITCH) + (i & 1) * (IMG_PITCH / 4) + ((i % 6) >> 1) * 32);
    if (wq == 0) { local_softmax<0>(s[0], p[0], row0 - 16, lane, sel); local_softmax<0>(s[1], p[1], 0, lane, sel); }
    else if (wq == 1) { local_softmax<1>(s[0], p[0], 0, lane, sel); local_softmax<1>(s[1], p[1], 0, lane, sel); }
    else if (wq == 2) { local_softmax<2>(s[0], p[0], 0, lane, sel); local_softmax<2>(s[1], p[1], 0, lane, sel); }
    else { local_softmax<3>(s[0], p[0], 0, lane, sel); local_softmax<3>(s[1], p[1], 0, lane, sel); }
  }
  pin(p[0]); pin(p[1]);
  wg_fence();
#pragma unroll
  for (int f = 0; f < 2; f++) {
    wgmma_rs_n24_mn0(o[f], p[f][0], p[f][1], p[f][2], p[f][3], vd + f * (LBUF / 16));
#pragma unroll
    for (int k = 1; k < 5; k++) wgmma_rs_n24_mn<1>(o[f], p[f][4 * k], p[f][4 * k + 1], p[f][4 * k + 2], p[f][4 * k + 3], vd + f * (LBUF / 16) + k * 48);
  }
  wg_commit();
  wg_wait<0>(); pin(o[0]); pin(o[1]); pin(p[0]); pin(p[1]);
}
__device__ __forceinline__ void group_table(uint32_t sb, int quarter, int lane) {
#pragma unroll
  for (int g = lane; g < 64; g += 32) {
    const int e = quarter * 32 + (g & 31);
    sts32(sb + SM_M + g * 4, ((e / 10) * 20 + e % 10 + (g >> 5) * 10) * 128);
  }
}

__global__ void __launch_bounds__(384, 1) km_fused(const __grid_constant__ Maps mp, const __nv_bfloat16* __restrict__ x,
                                                   const __nv_bfloat16* __restrict__ gate_w, const uint8_t* wA, const uint8_t* wB, const uint8_t* woA, const uint8_t* woB, uint32_t k16) {
  extern __shared__ __align__(1024) uint8_t sp[];
  constexpr uint32_t sb = 1024;
  constexpr uint32_t bars = sb + SM_BAR;
  volatile uint32_t* s_chk = (volatile uint32_t*)(sp + SM_M + 256);
  volatile uint32_t* s_epoch = (volatile uint32_t*)(sp + SM_M + 320);
  const int tid = threadIdx.x;
  const int warp = __shfl_sync(~0u, tid >> 5, 0), lane = tid & 31;
  const int wg = warp >> 2, wq = warp & 3, bid = blockIdx.x;
  const int h = bid >> 2, R0 = (bid & 3) * 512;
  const int rt = bid >> 3, ct = bid & 7;
  const int ob = 127 - bid - ((127 - bid) >> 4), ft = ob % 9, tt = ob / 9;
  const bool has_out = (bid & 15) != 0 && bid > 3;
  const int a1 = 3 * ct + ((rt & 2) ? 9 : 0), c1 = (a1 < 27 ? a1 : a1 - 27) * 64;
  if (tid < 16 || (tid >= 32 && tid < 56)) {
    const uint8_t* p = tid < 32 ? (const uint8_t*)x + (rt * 128 + ct * 16 + tid) * (DM * 2)
                                : wA + (((rt & 1) | (rt >> 2) << 1) * 8 + (tid & 7)) * (N3 * 2) + c1 * 2 + ((tid >> 3) & 3) * 128;
    asm volatile("prefetch.global.L2 [%0];" :: "l"(p));
  }

  if (wg == 2) {
    asm volatile("setmaxnreg.dec.sync.aligned.u32 56;");
    if (wq == 0) {
      if (elect_one()) {
        mbar_init(bars + 8 * B_X, 1); mbar_init(bars + 8 * B_WF, 1);
        asm volatile("fence.mbarrier_init.release.cluster;" ::: "memory");
        load_x(mp, sb, 0, rt); load_w1(mp, sb, 0, 0, c1);
#pragma unroll
        for (int i = 1; i < B_WE; i++) if (i != B_WF) mbar_init(bars + 8 * i, 1);
        asm volatile("fence.mbarrier_init.release.cluster;" ::: "memory");
        load_w1(mp, sb, 1, 1, c1);
      }
      __syncwarp();
      asm volatile("bar.arrive 8, 384;" ::: "memory");
      if (elect_one()) { load_x(mp, sb, 1, rt); load_w1(mp, sb, 2, 2, c1); load_w1(mp, sb, 3, 3, c1); load_x(mp, sb, 2, rt); load_w1(mp, sb, 4, 4, c1); }
      named_sync(7, 64);
      int s = 0, ph = 0;
#pragma unroll 1
      for (int it = 5; it < 18; it++) {
        if (!(it & 1) && elect_one()) load_x(mp, sb, it >> 1, rt);
        mbar_wait(bars + 8 * (B_WE + s), ph);
        if (elect_one()) load_w1(mp, sb, it, s, c1);
        if (++s == 5) { s = 0; ph ^= 1; }
      }
      const CUtensorMap* m3 = ct ? &mp.wB : &mp.wA;
      const int c2 = ct ? (4 * ct - 3) * 64 : ((rt & 2) ? 6 : 24) * 64;
#pragma unroll 1
      for (int it = 0; it < 18; it++) {
        const uint32_t bar = bars + 8 * (B_W2F + (it & 3)), dst = sb + SM_W + ((it + 2) & 3) * 16384;
        if (it < 3) mbar_wait(bars + 8 * (B_WE + (it ? 2 * it - 2 : 4)), it ? 1 : 0);
        mbar_wait(bars + 8 * (B_W2E + (it & 3)), ((it >> 2) & 1) ^ 1);
        if (elect_one()) {
          mbar_expect(bar, 16384);
#pragma unroll
          for (int a = 0; a < 3; a++) tma2d(dst + a * 4096, m3, c2 + a * 64, it * 32, bar);
          tma2d(dst + 12288, &mp.wB, ct * 256, it * 32, bar);
        }
      }
      await(&g_cnt[C_T1], *s_epoch * 128);
      if (elect_one()) { load_kv(mp, sb, 0, h, true); load_kv(mp, sb, 1, h); }
    } else {
      if (wq == 1) {
        if (elect_one()) {
          if (smem_u32(sp) != sb) __trap();
          sts32(sb + SM_M + 324, 0); sts64(sb + SM_M + 328, 0x3F003F00u, 0x3F003F00u);
#pragma unroll
          for (int i = B_WE; i < B_COUNT; i++)
            mbar_init(bars + 8 * i, i < B_K0 ? 8 : i >= B_FR ? 4 : i >= B_W2E ? 8 : 1);
          asm volatile("fence.mbarrier_init.release.cluster;" ::: "memory");
        }
        __syncwarp();
        asm volatile("bar.arrive 7, 64;" ::: "memory");
      }
      named_sync(8, 384);
      if (wq == 1) {
        if (lane == 0) *s_epoch = __ldcg(&g_epoch[bid]) + 1;
        group_table(sb, bid & 3, lane);
        if (elect_one()) { l2_prefetch(wB + bid * 15552, 15552); tm_prefetch(&mp.wB); tm_prefetch(&mp.img32); }
      } else {
        mbar_sleep(bars + 8 * B_X, 0);
        const int row = bid * 16 + (wq - 2) * 8 + (lane >> 2);
        const uint4* xr = (const uint4*)(x + row * DM) + (lane & 3);
        const uint4* gw = (const uint4*)gate_w + (lane & 3);
        float s = 0.f;
#pragma unroll 3
        for (int i = 0; i < 18; i++) {
          const uint4 a = __ldg(xr + 4 * i), b = __ldg(gw + 4 * i);
          const uint32_t p0 = hmul2(a.x, b.x), p1 = hmul2(a.y, b.y), p2 = hmul2(a.z, b.z), p3 = hmul2(a.w, b.w);
          s += ((bf_lo(p0) + bf_hi(p0)) + (bf_lo(p1) + bf_hi(p1))) + ((bf_lo(p2) + bf_hi(p2)) + (bf_lo(p3) + bf_hi(p3)));
        }
        s += __shfl_xor_sync(~0u, s, 1); s += __shfl_xor_sync(~0u, s, 2);
        if ((lane & 3) == 0) {
          const float g = bf_round(1.f / (1.f + __expf(-bf_round(s))));
          g_gate[row] = pack_bf16(g, 1.f - g);
        }
      }
      if (wq == 1) {
        const int slice0 = (96 * ct) / 9, phi = 96 * ct - 9 * slice0;
#pragma unroll 1
        for (int u = 0; u < 6; u++) {
          const int q = u > 2 ? u - 3 : u, sf = q ? (phi + 32 * q - 4) / 9 : 0, m0 = q ? cm_of(phi + 32 * q) : (phi + 3) >> 2, m1 = cm_of(phi + 32 * q + 32);
          uint8_t* dst = g_img + (size_t)(rt * 16 + (u > 2)) * IMG_PITCH + slice0 * GRP + m0 * 128;
          const uint32_t src = __shfl_sync(~0u, piece_buf(sb, u, 0) - sf * GRP + m0 * 128, 0), sw = __shfl_sync(~0u, piece_buf(0, u, 1) - piece_buf(0, u, 0), 0);
          mbar_sleep(bars + 8 * (B_P + u), 0);
          if (elect_one()) {
#pragma unroll
            for (int w = 0; w < 8; w++) {
              bulk_s2g(dst + (size_t)w * 2 * IMG_PITCH, src + w * sw, (m1 - m0) * 128);
              bulk_commit();
              asm volatile("cp.async.bulk.wait_group.read 5;" ::: "memory");
            }
            if (u == 0) { bulk_wait_read(); mbar_arrive(bars + 8 * B_F); }
            if (u == 2) mbar_arrive(bars + 8 * (B_F + 1));
          }
        }
        named_sync(2, 96);
        bulk_wait_all();
        if (elect_one()) red_add(&g_cnt[C_T1]);
      } else {
        mbar_sleep(bars + 8 * (B_P + 1), 0);
        asm volatile("fence.acq_rel.gpu;" ::: "memory");
        named_sync(2, 96);
      }
    }
    __syncwarp();
    named_sync(3, 128);

    const uint32_t epoch = *s_epoch, sgate = sb + SM_G;
    const int t7 = tid & 127;
    uint32_t mx[3] = {0, 0, 0};
    mbar_sleep(bars + 8 * B_K0, 0);
#pragma unroll
    for (int i = 0; i < 2; i++) mx[0] = row_norm2_max(mx[0], sp + SM_Q + ((t7 >> 3) + 16 * i) * GRP + (t7 & 7) * 16);
    {
      const int P0 = 768 + 128 * ct, slice2 = P0 / 9, phi = P0 - 9 * slice2, m0 = (phi + 3) >> 2, m1 = cm_of(phi + min(128, 1728 - P0));
      uint8_t* dst = g_img + (size_t)(rt * 16 + wq * 4) * IMG_PITCH + slice2 * GRP + m0 * 128;
      mbar_sleep(bars + 8 * (B_S2 + (wq >> 1)), 0);
      fence_async_global();
      if (elect_one()) {
        if (wq >= 2) load_kv(mp, sb, 2 + wq, h);
#pragma unroll
        for (int i = 0; i < 4; i++) bulk_s2g(dst + (size_t)i * IMG_PITCH, sb + (2 + (wq & 2) * 2 + (wq & 1)) * KVST + i * 6144 + m0 * 128, (m1 - m0) * 128);
        bulk_commit();
        if (wq & 1) asm volatile("fence.acq_rel.gpu;" ::: "memory");
        bulk_wait_all();
      }
      named_sync(3, 128);
      if (wq == 3) {
        if (elect_one()) red_add(&g_cnt[C_T2]);
        await(&g_cnt[C_T2], epoch * 128);
        if (elect_one()) load_kv(mp, sb, 2, h);
      }
      if (wq == 0) { mbar_sleep(bars + 8 * B_QR, 0); fence_async(); }
      named_sync(3, 128);
      fence_async_global();
      if (elect_one()) {
        if (wq) load_kv(mp, sb, 2 + (wq & 2) * 2 + (wq & 1), h);
        if (wq == 0) {
          mbar_expect(bars + 8 * B_Q2, 32 * GRP + 2048);
          tma2d(sb + SM_Q, &mp.img32, (64 + h) * 192, (R0 >> 3) + 32, bars + 8 * B_Q2);
          bulk_g2s(sb + SM_G, g_gate + R0, 2048, bars + 8 * B_Q2);
        }
        if (wq == 2) load_local(mp, sb + SM_L, bars + 8 * B_L, h, R0);
        if (wq & 1) l2_prefetch((wq == 1 ? woA : woB) + bid * 5184, 5184);
      }
    }
    __syncwarp();
    asm volatile("setmaxnreg.inc.sync.aligned.u32 168;");
#pragma unroll
    for (int j = 0; j < 2; j++) {
      const int sl = (bid & 2) * 2 + (bid & 1) + 2 * j;
      mbar_sleep(bars + 8 * (B_KV + sl), 0);
#pragma unroll
      for (int i = 0; i < 4; i++) mx[1 + (i >> 1)] = row_norm2_max(mx[1 + (i >> 1)], sp + SM_KV + sl * KVST + ((t7 >> 3) + 16 * i) * GRP + (t7 & 7) * 16);
    }
    mbar_sleep(bars + 8 * B_Q2, 0);
#pragma unroll
    for (int i = 0; i < 2; i++) mx[0] = row_norm2_max(mx[0], sp + SM_Q + ((t7 >> 3) + 16 * i) * GRP + (t7 & 7) * 16);
#pragma unroll
    for (int i = 0; i < 3; i++) { mx[i] = __reduce_max_sync(~0u, mx[i] >> 16); if (lane == 0) s_chk[4 * i + wq] = mx[i]; }
    named_sync(3, 128);
    if (wq == 1) {
      uint32_t m[3];
#pragma unroll
      for (int i = 0; i < 3; i++) m[i] = max(max(s_chk[4 * i], s_chk[4 * i + 1]), max(s_chk[4 * i + 2], s_chk[4 * i + 3]));
      if (lane == 0) asm volatile("st.relaxed.gpu.global.u64 [%0], %1;" :: "l"(&g_nrm[bid]), "l"((uint64_t)(m[1] | m[2] << 16) << 32 | epoch) : "memory");
      uint64_t tv; int it = 0;
      do { asm volatile("ld.relaxed.gpu.global.u64 %0, [%1];" : "=l"(tv) : "l"(&g_nrm[(bid & ~3) + (lane & 3)]) : "memory");
      } while (__any_sync(~0u, (uint32_t)tv != epoch) && ++it < (1 << 20));
      const uint32_t v = (uint32_t)(tv >> 32);
      const float q2 = bf_lo(m[0]), k2 = bf_lo(__reduce_max_sync(~0u, v & 0xFFFF)), v2 = bf_lo(__reduce_max_sync(~0u, v >> 16));
      if (lane == 0) {
        s_chk[12] = 1.05f * QSCALE * ex2(0.5f * (__log2f(q2) + __log2f(k2))) + 0.5f * fabsf(__log2f(v2)) + 2.1f <= 110.f ? 0 : 1;
        mbar_arrive(bars + 8 * B_CK);
      }
    }
    __syncwarp();
    {
      uint32_t q[2][8], p[2][20]; float o[2][12];
      const uint32_t z = lds32(sb + SM_M + 324);
#pragma unroll
      for (int i = 0; i < 20; i++) { p[0][i] = z; p[1][i] = z; }
      const uint64_t kd = mkdesc(sb + SM_L, 128, GRP, 0) + blockIdx.y, vd = mkdesc(sb + SM_L + 10 * GRP, GRP, 128, 0) + blockIdx.y;
      const bool par = (lane >> 2) & 1, lo = (lane & 3) * 2 > ((lane >> 2) & ~1);
      const uint32_t outer = par ? 0x1044 : 0x4410;
      const uint3 sel = make_uint3(lo ? outer : 0x4444, lo ? 0x4444 : outer, par ? 0x3244 : 0x4432);
      const uint32_t* qn = (const uint32_t*)(g_img + (size_t)((R0 >> 3) + wq * 2) * IMG_PITCH + (96 + h) * GRP) + lane;
      mbar_sleep(bars + 8 * B_L, 0);
      fence_async_global();
      load_q_global(q[0], 96 + h, R0 + wq * 16, lane); load_q_global(q[1], 96 + h, R0 + 64 + wq * 16, lane);
      q[0][6] = q[0][7] = q[1][6] = q[1][7] = z;
#pragma unroll 1
      for (int i = 0; i < 4; i++) {
        if (i < 3) qn += 4 * IMG_PITCH;
        mbar_sleep(bars + 8 * B_L, i & 1);
        local_pair(o, q, p, kd, vd, R0 + i * 128, qn, wq, lane, sel);
        named_sync(3, 128);
        if (i < 3 && wq == i && elect_one()) load_local(mp, sb + SM_L, bars + 8 * B_L, h, R0 + (i + 1) * 128);
        store_o<1>(o, i * 128 + wq * 16, h, sgate, lane);
      }
      named_sync(3, 128);
    }
    if (wq == 3 && elect_one()) signal(&g_cnt[C_LOC]);
    if (wq == 1) { mbar_sleep(bars + 8 * B_J0, 0); if (elect_one()) signal(&g_cnt[C_EARLY]); }
    if (has_out) {
      if (wq < 3) {
        mbar_sleep(bars + 8 * (B_SF + wq), 0);
        if (elect_one()) load_wo(mp, sb + wq * KVST, 1, wq, ft, bars + 8 * (B_WO + wq));
      } else {
        await2(&g_cnt[C_LOC], &g_cnt[C_EARLY], epoch * 128);
        mbar_sleep(bars + 8 * B_SF, 0);
        fence_async();
        if (elect_one()) { load_o<0>(mp, sb, tt); load_o<13>(mp, sb, tt); tm_prefetch(&mp.woMainA); tm_prefetch(&mp.woTailA); tm_prefetch(&mp.out); tm_prefetch(&mp.o10); }
      }
      named_sync(3, 128);
      mbar_sleep(bars + 8 * (B_SF + 3 + wq), 0);
      fence_async_global();
      if (elect_one()) {
        const uint32_t bar = bars + 8 * (B_OF + 1 + wq);
        mbar_expect(bar, OBLK);
        tma3d(sb + SM_O + wq * OBLK, &mp.o20, 0, tt * 20, 80 + wq * 8, bar);
      }
      float accE[40], accL[40];
#pragma unroll
      for (int i = 0; i < 40; i++) { accE[i] = 0.f; accL[i] = 0.f; }
      pin(accE); pin(accL);
      const uint64_t dA = mkdesc(sb, 16, 1024, 1), dB = mkdesc(sb + SM_O, 2560, 128, 0), dC = mkdesc(sb + SM_O, 1280, 128, 0);
      mbar_sleep(bars + 8 * B_WO, 0); mbar_sleep(bars + 8 * (B_WO + 1), 0); mbar_sleep(bars + 8 * (B_WO + 2), 0);
      mbar_sleep(bars + 8 * (B_SF + 7), 0);
      proj_b<0>(accE, accL, dA, dB, bars);
      proj_b<1>(accE, accL, dA, dB, bars); proj_b<2>(accE, accL, dA, dB, bars); proj_b<3>(accE, accL, dA, dB, bars);
      wg_wait<1>(); if (lane == 0) mbar_arrive(bars + 8 * (B_FR + 2));
      proj_b<4>(accE, accL, dA, dB, bars); proj_b<5>(accE, accL, dA, dB, bars); proj_b<6>(accE, accL, dA, dB, bars);
      wg_wait<1>(); if (lane == 0) mbar_arrive(bars + 8 * (B_FR + 3));
      proj_b<7>(accE, accL, dA, dB, bars); proj_b<8>(accE, accL, dA, dB, bars);
      mbar_wait(bars + 8 * (B_WO + 3), 0);
      proj_a<9>(accE, dA, dC, bars);
      wg_wait<1>(); if (lane == 0) mbar_arrive(bars + 8 * B_FR);
      mbar_wait(bars + 8 * (B_WO + 4), 0);
      proj_a<10>(accE, dA, dC, bars);
      wg_wait<0>(); if (lane == 0) mbar_arrive(bars + 8 * (B_FR + 1));
      proj_a<11>(accE, dA, dC, bars);
      mbar_wait(bars + 8 * (B_WO + 5), 0);
      proj_a<12>(accE, dA, dC, bars); proj_a<13>(accE, dA, dC, bars);
      wg_wait<0>(); pin(accE);
      named_sync(3, 128);
      proj_store(mp, accE, sb + SM_O + o_buf(11) * OBLK, 0, ft, tt, wq, lane);
      proj_a<14>(accL, dA, dC, bars);
      proj_a<15>(accL, dA, dC, bars); proj_a<16>(accL, dA, dC, bars); proj_a<17>(accL, dA, dC, bars); proj_a<18>(accL, dA, dC, bars);
      wg_wait<0>(); pin(accL);
      proj_store(mp, accL, sb + SM_O + o_buf(12) * OBLK, 1, ft, tt, wq, lane);
      bulk_wait_read();
    }
  } else {
    asm volatile("setmaxnreg.inc.sync.aligned.u32 224;");
    const uint64_t dX = mkdesc(sb + SM_X + wg * 8192, 16, 1024, 1);
    const uint64_t dW = mkdesc(sb + SM_W, 4096, 1024, 1);
    const int grp = rt * 16 + warp * 2;
    uint32_t off[9];
    float acc2[128];
    {
      uint32_t pk[48];
      float acc[96];
      const int slice0 = (96 * ct) / 9, phi = 96 * ct - 9 * slice0;
      make_off(off, phi, 0, lane);
      const int ty = ct / 3 + ((rt >> 1) & 1);
      uint32_t kp[4];
#pragma unroll
      for (int rh = 0; rh < 2; rh++) {
        const bool poly = (POLY_MASK >> ((grp + rh) & 7)) & 1;
        kp[2 * rh] = ty == 1 ? (poly ? ((lane & 1) ? 0x43F84780u : 0x42FE4780u) : 0x3F160000u) : ty == 2 ? 0x00003F80u : 0u;
        kp[2 * rh + 1] = ty == 1 ? (poly ? 0x00003B80u : 0x00003A00u) : 0u;
      }
      const uint32_t sh1 = ((phi + 28) / 9) * GRP, sh2 = ((phi + 60) / 9) * GRP;
      const bool e0 = cm_of(phi + (lane & 3)) < ((phi + 3) >> 2), e1 = cm_of(phi + 92 + (lane & 3)) >= cm_of(phi + 96);
      uint32_t eflag = (e0 ? 1 : 0) | (e1 ? 2 : 0);
      uint8_t* edst = g_img + (size_t)grp * IMG_PITCH + slice0 * GRP;
      pin(off); pin(kp);
      asm volatile("" : "+r"(eflag), "+l"(edst));
      named_sync(8, 384);
      {
        int s = 0, ph = 0;
#pragma unroll 1
        for (int it = 0; it < 18; it++) {
          if (!(it & 1)) mbar_wait(bars + 8 * (B_X + (it >> 1)), 0);
          mbar_wait(bars + 8 * (B_WF + s), ph);
          const uint64_t da = dX + (uint64_t)((it >> 1) * 1024 + (it & 1) * 4), db = dW + (uint64_t)((s ? s - 1 : 4) * 768);
          wg_fence();
          wgmma_ss_n192_mn(acc, da, db, it); wgmma_ss_n192_mn(acc, da + 2, db + 128, 1);
          wg_commit();
          wg_wait<1>();
          if (it > 0 && lane == 0) mbar_arrive(bars + 8 * (B_WE + (s ? s - 1 : 4)));
          if (++s == 5) { s = 0; ph ^= 1; }
        }
        wg_wait<0>(); pin(acc);
        if (lane == 0) mbar_arrive(bars + 8 * (B_WE + 2));
        pack_acc(pk, acc);
        pin(pk);
      }
#define PIECE(U) piece_stage<U>(pk, off, piece_buf(sb, U, warp), U % 3 == 0 ? 0 : U % 3 == 1 ? sh1 : sh2, kp[2 * (U / 3)], kp[2 * (U / 3) + 1], lane)
#define STEP(IT, ...) proj2_step<IT>(acc2, dX, dW, bars); __VA_ARGS__; proj2_done<IT>(bars, lane)
      STEP(0, PIECE(0));
      STEP(1, piece_hand(0, bars, lane));
      STEP(2, if (eflag & 1) { *(uint32_t*)(edst + off[0]) = pk[0]; *(uint32_t*)(edst + IMG_PITCH + off[0]) = pk[1]; }
              if (eflag & 2) { *(uint32_t*)(edst + off[5] + 8 * GRP) = pk[46]; *(uint32_t*)(edst + IMG_PITCH + off[5] + 8 * GRP) = pk[47]; });
      STEP(3, PIECE(1));
      STEP(4, piece_hand(1, bars, lane));
      STEP(5, mbar_wait(bars + 8 * B_F, 0); PIECE(2); PIECE(3));
      STEP(6, piece_hand(2, bars, lane); if (lane == 0) mbar_arrive(bars + 8 * (B_P + 3)));
      STEP(7, PIECE(4));
      STEP(8, piece_hand(4, bars, lane); mbar_wait(bars + 8 * (B_F + 1), 0); PIECE(5));
      STEP(9, piece_hand(5, bars, lane));
    }
    const int P0 = 768 + 128 * ct, slice2 = P0 / 9, phi = P0 - 9 * slice2, np = min(128, 1728 - P0);
    const uint32_t stg = sb + (2 + 4 * wg) * KVST + wq * 2 * 6144;
    uint32_t padv[4], eflag;
    STEP(10, );
    STEP(11, make_off(off, phi, stg, lane); pin(off));
    STEP(12,
      _Pragma("unroll")
      for (int i = 0; i < 4; i++) { const int sl = slice2 + (lane >> 3) + 4 * i; padv[i] = (sl >= 160 || (sl < 96 && !(rt & 2))) ? 0x00003F80u : 0u; }
      eflag = (cm_of(phi + (lane & 3)) < ((phi + 3) >> 2) ? 1 : 0) | (np == 128 && cm_of(phi + 124 + (lane & 3)) >= cm_of(phi + 128) ? 2 : 0);
      pin(padv); asm volatile("" : "+r"(eflag)));
    STEP(13, ); STEP(14, );
    if (wg == 1) named_sync(6, 256);
    proj2_step<15>(acc2, dX, dW, bars); proj2_step<16>(acc2, dX, dW, bars); proj2_step<17>(acc2, dX, dW, bars);
    if (wg == 0) asm volatile("bar.arrive 6, 256;" ::: "memory");
    wg_wait<0>(); pin(acc2);
    {
      uint32_t pk[64];
      if (wg == 0) asm volatile("bar.arrive 1, 256;" ::: "memory");
      pack_acc(pk, acc2);
      if (wg == 1) named_sync(1, 256);
#pragma unroll
      for (int rh = 0; rh < 2; rh++) {
        const uint32_t a = stg + rh * 6144 + (lane >> 3) * GRP + 256 + (lane & 7) * 16;
#pragma unroll
        for (int i = 0; i < 4; i++) sts128(a + i * 4 * GRP, 0, padv[i], 0, 0);
        __syncwarp();
#pragma unroll
        for (int j = 0; j < 32; j++) sts32(off[j % 9] + (j / 9) * 4 * GRP + rh * 6144, pk[2 * j + rh]);
      }
      fence_async();
      if (eflag & 1) edge_store(pk[0], pk[1], off[0] - stg, slice2, grp);
      if (eflag & 2) edge_store(pk[62], pk[63], off[4] - stg + 12 * GRP, slice2, grp);
      __syncwarp();
      if (lane == 0) mbar_arrive(bars + 8 * (B_S2 + wg));
    }
    asm volatile("setmaxnreg.dec.sync.aligned.u32 168;");

    const uint64_t kd0 = mkdesc(sb + SM_KV, 128, GRP, 0), vd0 = mkdesc(sb + SM_KV + 12288, GRP, 128, 0);
    const uint32_t sgate = sb + SM_G;
    uint32_t khalf;
    asm volatile("{\n.reg .b32 t;\nld.volatile.shared.v2.u32 {t, %0}, [%1];\n}" : "=r"(khalf) : "r"(sb + SM_M + 328) : "memory");
    bool slow = false;
#pragma unroll 1
    for (int job = 0; job < 2; job++) {
      const int relA = job * 256 + wg * 128 + wq * 16;
      uint32_t qa[8], qb[8];
      float o2[2][12], sA[32], sB[32]; uint32_t pA[16], pB[16];
      float (&oa)[12] = o2[0]; float (&ob)[12] = o2[1];
#pragma unroll
      for (int i = 0; i < 12; i++) { oa[i] = 0.f; ob[i] = 0.f; }
#pragma unroll
      for (int i = 0; i < 32; i++) { sA[i] = 0.f; sB[i] = 0.f; }
      mbar_wait(bars + 8 * B_K0, 0);
      { const uint32_t a = sb + SM_Q + (wg * 16 + wq * 2) * GRP + lane * 4; load_q_shared(qa, a); load_q_shared(qb, a + 8 * GRP); }
      { const uint32_t ext = (lane & 3) == 1 ? 0x3F803F80u : (lane & 3) == 2 ? 0x00003F80u : 0u; scale_q(qa, ext, lane); scale_q(qb, ext, lane); }
      pin(oa); pin(ob); pin(sA); pin(sB); pin(qa); pin(qb);
      wg_fence(); issue_S(sA, qa, kd0); wg_commit();
      if (job == 0 && lane == 0) mbar_arrive(bars + 8 * B_QR);
      wg_wait<0>(); pin(sA);
      if (job == 0) mbar_wait(bars + 8 * B_KV, 0);
#pragma unroll 1
      for (int st = 0, nx; st < 8; st = nx) {
        nx = job ? st + 2 : (0x8020604 >> (4 * st)) & 15;
        uint64_t kb = kd0 + (uint64_t)(uint32_t)(st * 1536), vb = vd0 + (uint64_t)(uint32_t)(st * 1536), kn = kd0 + (uint64_t)(uint32_t)(nx * 1536);
        asm volatile("" : "+l"(kb), "+l"(vb), "+l"(kn));
        const uint32_t nb[2] = {bars + 8 * (B_KV + st + 1), bars + 8 * (B_KV + nx)};
        uint32_t ready = 1;
        wg_fence(); issue_S(sB, qb, kb); wg_commit();
#pragma unroll
        for (int u = 0; u < 8; u++) {
          const int co = (u >> 2) * 1536 + (u & 3) * 192, cn = ((u + 1) >> 2) * 1536 + ((u + 1) & 3) * 192;
          if (u > 0) { wg_wait<1>(); pin(sA); }
          if (u > 4 && (u & 3) == 1 && job == 1 && lane == 0) mbar_arrive(bars + 8 * (B_SF + st + (u >> 2) - 1));
          if ((u & 3) == 2) ready = mbar_test(nb[u >> 2], 0);
          if ((u & 3) == 3 && !ready) mbar_wait(nb[u >> 2], 0);
          softmax64(sA, pA, khalf, k16);
          pin(pA);
          wg_fence();
          issue_PV(oa, pA, vb + co);
          issue_S(sA, qa, u < 7 ? kb + cn : kn);
          wg_commit();
          wg_wait<1>(); pin(sB);
          softmax64(sB, pB, khalf, k16);
          pin(pB);
          wg_fence();
          issue_PV(ob, pB, vb + co);
          if (u < 8 - 1) issue_S(sB, qb, kb + cn);
          wg_commit();
        }
        wg_wait<0>(); pin(sA); pin(oa); pin(ob);
        if (job == 1 && lane == 0) mbar_arrive(bars + 8 * (B_SF + st + 1));
      }
      if (job == 0) {
        slow = __any_sync(~0u, lds32(sb + SM_M + 256 + 48) != 0);
        if (slow) break;
      }
      store_o<0>(o2, relA, h, sgate, lane);
      if (job == 0) { __syncwarp(); if (lane == 0) mbar_arrive(bars + 8 * B_J0); }
    }
    if (slow) {
#pragma unroll 1
      for (int tile = wg; tile < 8; tile += 2) {
        const int rel = tile * 64 + wq * 16;
        uint32_t q[8];
        load_q_global(q, slice_q(tile >> 2) + h, R0 + rel, lane);
        if (lane & 3) { q[4] = 0; q[5] = 0; }
        float o1[1][12], s[32]; uint32_t p[16];
        float (&o)[12] = o1[0];
#pragma unroll
        for (int i = 0; i < 12; i++) o[i] = 0.f;
#pragma unroll
        for (int i = 0; i < 32; i++) s[i] = 0.f;
        float m0 = __int_as_float(0xff800000), m1 = m0;
#pragma unroll 1
        for (int c = 0; c < 32; c++) {
          const uint64_t co = (uint64_t)((c >> 2) * 1536 + (c & 3) * 192);
          pin(s); pin(q);
          wg_fence(); issue_S(s, q, kd0 + co); wg_commit(); wg_wait<0>(); pin(s);
          float n0 = m0, n1 = m1;
#pragma unroll
          for (int b = 0; b < 8; b++) { n0 = fmaxf(n0, fmaxf(s[4 * b], s[4 * b + 1])); n1 = fmaxf(n1, fmaxf(s[4 * b + 2], s[4 * b + 3])); }
          n0 = fmaxf(n0, __shfl_xor_sync(~0u, n0, 1)); n1 = fmaxf(n1, __shfl_xor_sync(~0u, n1, 1));
          n0 = fmaxf(n0, __shfl_xor_sync(~0u, n0, 2)); n1 = fmaxf(n1, __shfl_xor_sync(~0u, n1, 2));
          const float a0 = ex2((m0 - n0) * QSCALE), a1 = ex2((m1 - n1) * QSCALE);
          m0 = n0; m1 = n1;
#pragma unroll
          for (int b = 0; b < 3; b++) { o[4 * b] *= a0; o[4 * b + 1] *= a0; o[4 * b + 2] *= a1; o[4 * b + 3] *= a1; }
#pragma unroll
          for (int b = 0; b < 8; b++) {
            p[2 * b] = pack_bf16(ex2((s[4 * b] - m0) * QSCALE), ex2((s[4 * b + 1] - m0) * QSCALE));
            p[2 * b + 1] = pack_bf16(ex2((s[4 * b + 2] - m1) * QSCALE), ex2((s[4 * b + 3] - m1) * QSCALE));
          }
          pin(o); pin(p);
          wg_fence(); issue_PV(o, p, vd0 + co); wg_commit(); wg_wait<0>(); pin(o);
        }
        store_o<0>(o1, rel, h, sgate, lane);
      }
      __syncwarp();
      if (lane == 0) for (int i = 0; i < 9; i++) mbar_arrive(bars + 8 * (B_J0 + i));
    }
    named_sync(4, 256);
    const uint32_t epoch = *s_epoch;
    if (warp == 1 && elect_one()) {
      signal(&g_flag[(bid & 3) * 32 + (h >> 3)]);
      g_epoch[bid] = epoch;
    }
    if (has_out && warp == 2) {
      mbar_wait(bars + 8 * B_OF, 0);
      fence_async_global();
      if (elect_one()) { load_o<5>(mp, sb, tt); load_o<6>(mp, sb, tt); }
      mbar_wait(bars + 8 * (B_FR + 2), 0);
      if (elect_one()) { load_wo(mp, sb, 0, 0, ft, bars + 8 * (B_WO + 3)); load_o<7>(mp, sb, tt); load_o<8>(mp, sb, tt); load_o<9>(mp, sb, tt); }
      mbar_wait(bars + 8 * (B_FR + 3), 0);
      if (elect_one()) { load_wo(mp, sb + KVST, 0, 1, ft, bars + 8 * (B_WO + 4)); load_o<10>(mp, sb, tt); load_o<11>(mp, sb, tt); load_o<12>(mp, sb, tt); }
      mbar_wait(bars + 8 * B_FR, 0);
      if (elect_one()) load_wo(mp, sb + 2 * KVST, 0, 2, ft, bars + 8 * (B_WO + 5));
    }
    if (has_out && warp == 0) {
      const uint32_t* f0 = &g_flag[(((lane & 4) ? min(tt * 10 + 9, 127) : tt * 10) >> 5) * 32 + (lane & 3)];
      uint32_t todo = 15;
      int pos = 0, it = 0;
      mbar_wait(bars + 8 * B_FR, 0);
#pragma unroll 1
      while (todo && ++it < (1 << 20)) {
        uint32_t a;
        asm volatile("ld.relaxed.gpu.global.u32 %0, [%1];" : "=r"(a) : "l"(f0) : "memory");
        const uint32_t m = __ballot_sync(~0u, (int)(a - epoch * 8) >= 0);
        uint32_t rdy = todo & m & (m >> 4);
        todo &= ~rdy;
        if (rdy) {
          asm volatile("fence.acquire.gpu;\nfence.proxy.async.global;" ::: "memory");
        }
#pragma unroll 1
        for (; rdy; rdy &= rdy - 1, pos++) {
          const int j = __ffs(rdy) - 1;
          if (pos == 3) mbar_wait(bars + 8 * (B_FR + 1), 0);
          if (elect_one()) {
            const uint32_t bar = bars + 8 * (B_OF + 14 + pos);
            sts32(sb + SM_M + 336 + 4 * pos, j);
            mbar_expect(bar, OBLK);
            tma3d(sb + SM_O + (((o_buf(14) | o_buf(15) << 4 | o_buf(16) << 8 | o_buf(17) << 12) >> (4 * pos)) & 15) * OBLK, &mp.o10, 0, tt * 20 + 10, j * 16, bar);
          }
        }
      }
      if (elect_one()) load_o<18>(mp, sb, tt);
    }
  }
}

typedef CUresult (*EncodeFn)(CUtensorMap*, CUtensorMapDataType, cuuint32_t, void*, const cuuint64_t*, const cuuint64_t*, const cuuint32_t*,
                             const cuuint32_t*, CUtensorMapInterleave, CUtensorMapSwizzle, CUtensorMapL2promotion, CUtensorMapFloatOOBfill);
static void make_map(EncodeFn fn, CUtensorMap* tm, void* ptr, int rank, const uint64_t (&d)[3], const uint64_t (&st)[2], const uint32_t (&b)[3], bool swz) {
  cuuint64_t dims[3] = {d[0], d[1], d[2]}, strides[2] = {st[0], st[1]};
  cuuint32_t box[3] = {b[0], b[1], b[2]}, es[3] = {1, 1, 1};
  fn(tm, CU_TENSOR_MAP_DATA_TYPE_BFLOAT16, rank, ptr, dims, strides, box, es, CU_TENSOR_MAP_INTERLEAVE_NONE,
     swz ? CU_TENSOR_MAP_SWIZZLE_128B : CU_TENSOR_MAP_SWIZZLE_NONE, CU_TENSOR_MAP_L2_PROMOTION_L2_128B, CU_TENSOR_MAP_FLOAT_OOB_FILL_NONE);
}

extern "C" void kernel_launch(void* const* d_in, const int* in_sizes, int n_in, void* d_out, int out_size) {
  static Maps mp;
  static void* seen[8] = {};
  bool same = seen[7] == d_out;
  for (int i = 0; i < 7; i++) same = same && seen[i] == d_in[i];
  if (!same) {
    void* fp = nullptr; cudaDriverEntryPointQueryResult qr;
    cudaGetDriverEntryPoint("cuTensorMapEncodeTiled", &fp, cudaEnableDefault, &qr);
    EncodeFn fn = (EncodeFn)fp;
    void *po = nullptr, *pi = nullptr;
    cudaGetSymbolAddress(&po, g_o); cudaGetSymbolAddress(&pi, g_img);
    make_map(fn, &mp.x, d_in[0], 2, {DM, SEQ, 1}, {DM * 2, 0}, {64, 128, 1}, true);
    make_map(fn, &mp.wA, d_in[1], 2, {N3, DM, 1}, {N3 * 2, 0}, {64, 32, 1}, true);
    make_map(fn, &mp.wB, d_in[4], 2, {N3, DM, 1}, {N3 * 2, 0}, {64, 32, 1}, true);
    make_map(fn, &mp.img32, pi, 2, {IMG_PITCH / 2, 256, 1}, {IMG_PITCH, 0}, {192, 32, 1}, false);
    make_map(fn, &mp.img10, pi, 2, {IMG_PITCH / 2, 256, 1}, {IMG_PITCH, 0}, {192, 10, 1}, false);
    make_map(fn, &mp.o20, po, 3, {64, NVG, 144}, {128, NVG * 128}, {64, 20, 8}, false);
    make_map(fn, &mp.o10, po, 3, {64, NVG, 144}, {128, NVG * 128}, {64, 10, 16}, false);
    make_map(fn, &mp.o10h, po, 3, {64, NVG, 144}, {128, NVG * 128}, {64, 10, 8}, false);
    make_map(fn, &mp.woMainA, d_in[2], 3, {DM, DH, 32}, {DM * 2, DH * DM * 2}, {64, 16, 4}, true);
    make_map(fn, &mp.woTailA, d_in[2], 3, {DM, DH, 32}, {DM * 2, DH * DM * 2}, {64, 2, 32}, true);
    make_map(fn, &mp.woMainB, d_in[5], 3, {DM, DH, 32}, {DM * 2, DH * DM * 2}, {64, 16, 4}, true);
    make_map(fn, &mp.woTailB, d_in[5], 3, {DM, DH, 32}, {DM * 2, DH * DM * 2}, {64, 2, 32}, true);
    make_map(fn, &mp.out, d_out, 2, {DM, SEQ, 1}, {DM * 2, 0}, {64, 8, 1}, true);
    cudaFuncSetAttribute(km_fused, cudaFuncAttributeMaxDynamicSharedMemorySize, SMEM_BYTES);
    for (int i = 0; i < 7; i++) seen[i] = d_in[i];
    seen[7] = d_out;
  }
  km_fused<<<128, 384, SMEM_BYTES, cudaStreamPerThread>>>(mp, (const __nv_bfloat16*)d_in[0], (const __nv_bfloat16*)d_in[6],
                                                           (const uint8_t*)d_in[1], (const uint8_t*)d_in[4], (const uint8_t*)d_in[2], (const uint8_t*)d_in[5], 65536u);
}
```
